```python
import torch

def _softmax(x, axis=-1):
    return torch.softmax(x, dim=axis)
def _gelu(x):
    return torch.nn.functional.gelu(x, approximate="tanh")
def _silu(x):
    return torch.nn.functional.silu(x)
def _sigmoid(x):
    return torch.sigmoid(x)
def _layernorm(x, axis=-1, eps=1e-5):
    m = x.mean(dim=axis, keepdim=True)
    v = x.var(dim=axis, keepdim=True, unbiased=False)
    return (x - m) / torch.sqrt(v + eps)
def _scatter_add(tgt, idx, src, axis=0):
    return tgt.clone().index_add_(axis, idx, src)
def _segment_sum(src, seg, n):
    out = torch.zeros((n,) + src.shape[1:], dtype=src.dtype)
    return out.index_add_(0, seg, src)
def _pad(x, pw):
    flat = tuple(v for pair in reversed(pw) for v in pair)
    return torch.nn.functional.pad(x, flat)

kernel_name = 'sequential_preLN__softmax_full_mha__dense_activation_gelu__prompt'

def setup_inputs():

    _w = (lambda a: (lambda t: t.to(torch.bfloat16) if t.is_floating_point() else t)(torch.as_tensor(a)))
    def _A_setup():
        B, S, D = 1, 2048, 1024
        return {
            "x": _w((lambda *s: torch.randn(*s, dtype=torch.bfloat16) * 0.05)(B, S, D)),
            "wqkv": _w((lambda *s: torch.randn(*s, dtype=torch.bfloat16) * 0.05)(D, 3 * D)),
            "wo": _w((lambda *s: torch.randn(*s, dtype=torch.bfloat16) * 0.05)(D, D)),
        }
    _A_in = _A_setup()

    def _B_setup():
        B, S, D, F = 1, 2048, 1024, 3584
        return {
            "x": _w((lambda *s: torch.randn(*s, dtype=torch.bfloat16) * 0.05)(B, S, D)),
            "w1": _w((lambda *s: torch.randn(*s, dtype=torch.bfloat16) * 3.2)(D, F) * (D ** -0.5)),
            "b1": _w((lambda *s: torch.randn(*s, dtype=torch.bfloat16) * 3.2)(F) * 0.01),
            "w2": _w((lambda *s: torch.randn(*s, dtype=torch.bfloat16) * 0.4)(F, D) * (F ** -0.5)),
            "b2": _w((lambda *s: torch.randn(*s, dtype=torch.bfloat16) * 0.4)(D) * 0.01),
        }
    _B_in = _B_setup()

    return {
        "A_x": _A_in["x"],
        "A_wqkv": _A_in["wqkv"],
        "A_wo": _A_in["wo"],
        "B_x": _B_in["x"],
        "B_w1": _B_in["w1"],
        "B_b1": _B_in["b1"],
        "B_w2": _B_in["w2"],
        "B_b2": _B_in["b2"],
    }

def reference(A_x, A_wqkv, A_wo, B_x, B_w1, B_b1, B_w2, B_b2):
    def _A_ref(x, wqkv, wo):
        B, S, D = x.shape
        H = 32; Dh = D // H
        qkv = (lambda x, *d: x.permute(*d))((x @ wqkv).reshape(B, S, 3, H, Dh), 2, 0, 3, 1, 4)
        q, k, v = qkv[0], qkv[1], qkv[2]
        scale = Dh ** -0.5
        scores = torch.einsum("bhqd,bhkd->bhqk", q, k) * scale
        p = _softmax(scores, axis=-1)
        o = torch.einsum("bhqk,bhkd->bhqd", p, v)
        return (lambda x, *d: x.permute(*d))(o, 0, 2, 1, 3).reshape(B, S, D) @ wo

    def _B_ref(x, w1, b1, w2, b2):
        h = torch.einsum("bsd,df->bsf", x, w1) + b1
        h = _gelu(h)
        return torch.einsum("bsf,fd->bsd", h, w2) + b2

    x = A_x
    h = x + _A_ref(_layernorm(x, axis=-1), A_wqkv, A_wo)
    h2 = h + _B_ref(_layernorm(h, axis=-1), B_w1, B_b1, B_w2, B_b2)
    return h2
```

```cpp
#include <cuda_runtime.h>
#include <cuda_bf16.h>
#include <cuda.h>
#include <stdint.h>

#define WAIT_TIMEOUT 0

namespace {

typedef __nv_bfloat16 bf16;

__device__ __forceinline__ uint32_t smem_u32(const void* p) {
  return (uint32_t)__cvta_generic_to_shared(p);
}
__device__ __forceinline__ void mbar_init(uint32_t bar, uint32_t count) {
  asm volatile("mbarrier.init.shared::cta.b64 [%0], %1;" ::"r"(bar), "r"(count) : "memory");
}
__device__ __forceinline__ void fence_mbar_init() {
  asm volatile("fence.mbarrier_init.release.cluster;" ::: "memory");
}
__device__ __forceinline__ void fence_proxy_async() {
  asm volatile("fence.proxy.async.shared::cta;" ::: "memory");
}
__device__ __forceinline__ void mbar_expect_tx(uint32_t bar, uint32_t bytes) {
  asm volatile("mbarrier.arrive.expect_tx.shared::cta.b64 _, [%0], %1;" ::"r"(bar), "r"(bytes) : "memory");
}
__device__ __forceinline__ void mbar_arrive(uint32_t bar) {
  asm volatile("mbarrier.arrive.shared::cta.b64 _, [%0];" ::"r"(bar) : "memory");
}
__device__ __forceinline__ uint32_t mbar_try_wait(uint32_t bar, uint32_t parity) {
  uint32_t ok;
  asm volatile(
      "{\n.reg .pred p;\n"
      "mbarrier.try_wait.parity.shared::cta.b64 p, [%1], %2;\n"
      "selp.u32 %0, 1, 0, p;\n}"
      : "=r"(ok) : "r"(bar), "r"(parity) : "memory");
  return ok;
}
__device__ __forceinline__ void mbar_wait(uint32_t bar, uint32_t parity) {
  while (!mbar_try_wait(bar, parity)) {}
}
__device__ __forceinline__ void named_bar_sync(int id, int nthreads) {
  asm volatile("bar.sync %0, %1;" ::"r"(id), "r"(nthreads) : "memory");
}
__device__ __forceinline__ void prefetch_tmap(const CUtensorMap* tm) {
  asm volatile("prefetch.tensormap [%0];" ::"l"(tm) : "memory");
}
__device__ __forceinline__ void tma_load_2d(uint32_t dst, const CUtensorMap* tm, int c0, int c1, uint32_t bar) {
  asm volatile(
      "cp.async.bulk.tensor.2d.shared::cluster.global.mbarrier::complete_tx::bytes [%0], [%1, {%3, %4}], [%2];"
      ::"r"(dst), "l"(tm), "r"(bar), "r"(c0), "r"(c1) : "memory");
}
__device__ __forceinline__ void tma_load_3d(uint32_t dst, const CUtensorMap* tm, int c0, int c1, int c2, uint32_t bar) {
  asm volatile(
      "cp.async.bulk.tensor.3d.shared::cluster.global.mbarrier::complete_tx::bytes [%0], [%1, {%3, %4, %5}], [%2];"
      ::"r"(dst), "l"(tm), "r"(bar), "r"(c0), "r"(c1), "r"(c2) : "memory");
}
__device__ __forceinline__ void tma_store_2d(const CUtensorMap* tm, uint32_t src, int c0, int c1) {
  asm volatile("cp.async.bulk.tensor.2d.global.shared::cta.bulk_group [%0, {%2, %3}], [%1];"
               ::"l"(tm), "r"(src), "r"(c0), "r"(c1) : "memory");
}
__device__ __forceinline__ void tma_store_commit() { asm volatile("cp.async.bulk.commit_group;" ::: "memory"); }
template <int N> __device__ __forceinline__ void tma_store_wait_read() {
  asm volatile("cp.async.bulk.wait_group.read %0;" ::"n"(N) : "memory");
}
__device__ __forceinline__ void wgmma_fence() { asm volatile("wgmma.fence.sync.aligned;" ::: "memory"); }
__device__ __forceinline__ void wgmma_commit() { asm volatile("wgmma.commit_group.sync.aligned;" ::: "memory"); }
template <int N> __device__ __forceinline__ void wgmma_wait() {
  asm volatile("wgmma.wait_group.sync.aligned %0;" ::"n"(N) : "memory");
}
template <int R> __device__ __forceinline__ void reg_alloc() {
  asm volatile("setmaxnreg.inc.sync.aligned.u32 %0;" ::"n"(R));
}
template <int R> __device__ __forceinline__ void reg_dealloc() {
  asm volatile("setmaxnreg.dec.sync.aligned.u32 %0;" ::"n"(R));
}
__device__ __forceinline__ void stmatrix_x4(uint32_t addr, uint32_t r0, uint32_t r1, uint32_t r2, uint32_t r3) {
  asm volatile("stmatrix.sync.aligned.m8n8.x4.shared.b16 [%0], {%1, %2, %3, %4};"
               ::"r"(addr), "r"(r0), "r"(r1), "r"(r2), "r"(r3) : "memory");
}
__device__ __forceinline__ void ldmatrix_x4(uint32_t addr, uint32_t& r0, uint32_t& r1, uint32_t& r2, uint32_t& r3) {
  asm volatile("ldmatrix.sync.aligned.m8n8.x4.shared.b16 {%0, %1, %2, %3}, [%4];"
               : "=r"(r0), "=r"(r1), "=r"(r2), "=r"(r3) : "r"(addr) : "memory");
}
__device__ __forceinline__ uint32_t pack_bf16(float lo, float hi) {
  uint32_t r;
  asm("cvt.rn.bf16x2.f32 %0, %1, %2;" : "=r"(r) : "f"(hi), "f"(lo));
  return r;
}
__device__ __forceinline__ float bf_lo(uint32_t p) { return __uint_as_float(p << 16); }
__device__ __forceinline__ float bf_hi(uint32_t p) { return __uint_as_float(p & 0xffff0000u); }
__device__ __forceinline__ float ex2_approx(float x) {
  float y;
  asm("ex2.approx.ftz.f32 %0, %1;" : "=f"(y) : "f"(x));
  return y;
}
__device__ __forceinline__ float tanh_approx(float x) {
  float y;
  asm("tanh.approx.f32 %0, %1;" : "=f"(y) : "f"(x));
  return y;
}
__device__ __forceinline__ void griddep_wait() { asm volatile("griddepcontrol.wait;" ::: "memory"); }
__device__ __forceinline__ void griddep_launch() { asm volatile("griddepcontrol.launch_dependents;" ::: "memory"); }
__device__ __forceinline__ unsigned ld_acquire(const unsigned* p) {
  unsigned v;
  asm volatile("ld.acquire.gpu.global.u32 %0, [%1];" : "=r"(v) : "l"(p) : "memory");
  return v;
}
__device__ __forceinline__ float warp_sum(float v) {
#pragma unroll
  for (int o = 16; o > 0; o >>= 1) v += __shfl_xor_sync(0xffffffffu, v, o);
  return v;
}
__device__ __forceinline__ uint64_t make_desc(uint32_t saddr, uint32_t lbo_bytes, uint32_t sbo_bytes, int swz  ) {
  uint64_t d = 0;
  d |= (uint64_t)((saddr & 0x3FFFF) >> 4);
  d |= (uint64_t)((lbo_bytes >> 4) & 0x3FFF) << 16;
  d |= (uint64_t)((sbo_bytes >> 4) & 0x3FFF) << 32;
  d |= (uint64_t)swz << 62;
  return d;
}

template <int TNSPB>
__device__ __forceinline__ void wgmma_ss_n128(float (&d)[64], uint64_t da, uint64_t db, int scale_d) {
  asm volatile("{\n.reg .pred p;\nsetp.ne.b32 p, %66, 0;\n"
    "wgmma.mma_async.sync.aligned.m64n128k16.f32.bf16.bf16 {%0, %1, %2, %3, %4, %5, %6, %7, %8, %9, %10, %11, %12, %13, %14, %15, %16, %17, %18, %19, %20, %21, %22, %23, %24, %25, %26, %27, %28, %29, %30, %31, %32, %33, %34, %35, %36, %37, %38, %39, %40, %41, %42, %43, %44, %45, %46, %47, %48, %49, %50, %51, %52, %53, %54, %55, %56, %57, %58, %59, %60, %61, %62, %63}, %64, %65, p, 1, 1, 0, %67;\n}"
    : "+f"(d[0]), "+f"(d[1]), "+f"(d[2]), "+f"(d[3]), "+f"(d[4]), "+f"(d[5]), "+f"(d[6]), "+f"(d[7]), "+f"(d[8]), "+f"(d[9]), "+f"(d[10]), "+f"(d[11]), "+f"(d[12]), "+f"(d[13]), "+f"(d[14]), "+f"(d[15]), "+f"(d[16]), "+f"(d[17]), "+f"(d[18]), "+f"(d[19]), "+f"(d[20]), "+f"(d[21]), "+f"(d[22]), "+f"(d[23]), "+f"(d[24]), "+f"(d[25]), "+f"(d[26]), "+f"(d[27]), "+f"(d[28]), "+f"(d[29]), "+f"(d[30]), "+f"(d[31]), "+f"(d[32]), "+f"(d[33]), "+f"(d[34]), "+f"(d[35]), "+f"(d[36]), "+f"(d[37]), "+f"(d[38]), "+f"(d[39]), "+f"(d[40]), "+f"(d[41]), "+f"(d[42]), "+f"(d[43]), "+f"(d[44]), "+f"(d[45]), "+f"(d[46]), "+f"(d[47]), "+f"(d[48]), "+f"(d[49]), "+f"(d[50]), "+f"(d[51]), "+f"(d[52]), "+f"(d[53]), "+f"(d[54]), "+f"(d[55]), "+f"(d[56]), "+f"(d[57]), "+f"(d[58]), "+f"(d[59]), "+f"(d[60]), "+f"(d[61]), "+f"(d[62]), "+f"(d[63])
    : "l"(da), "l"(db), "r"(scale_d), "n"(TNSPB));
}
template <int TNSPB>
__device__ __forceinline__ void wgmma_ss_n192(float (&d)[96], uint64_t da, uint64_t db, int scale_d) {
  asm volatile("{\n.reg .pred p;\nsetp.ne.b32 p, %98, 0;\n"
    "wgmma.mma_async.sync.aligned.m64n192k16.f32.bf16.bf16 {%0, %1, %2, %3, %4, %5, %6, %7, %8, %9, %10, %11, %12, %13, %14, %15, %16, %17, %18, %19, %20, %21, %22, %23, %24, %25, %26, %27, %28, %29, %30, %31, %32, %33, %34, %35, %36, %37, %38, %39, %40, %41, %42, %43, %44, %45, %46, %47, %48, %49, %50, %51, %52, %53, %54, %55, %56, %57, %58, %59, %60, %61, %62, %63, %64, %65, %66, %67, %68, %69, %70, %71, %72, %73, %74, %75, %76, %77, %78, %79, %80, %81, %82, %83, %84, %85, %86, %87, %88, %89, %90, %91, %92, %93, %94, %95}, %96, %97, p, 1, 1, 0, %99;\n}"
    : "+f"(d[0]), "+f"(d[1]), "+f"(d[2]), "+f"(d[3]), "+f"(d[4]), "+f"(d[5]), "+f"(d[6]), "+f"(d[7]), "+f"(d[8]), "+f"(d[9]), "+f"(d[10]), "+f"(d[11]), "+f"(d[12]), "+f"(d[13]), "+f"(d[14]), "+f"(d[15]), "+f"(d[16]), "+f"(d[17]), "+f"(d[18]), "+f"(d[19]), "+f"(d[20]), "+f"(d[21]), "+f"(d[22]), "+f"(d[23]), "+f"(d[24]), "+f"(d[25]), "+f"(d[26]), "+f"(d[27]), "+f"(d[28]), "+f"(d[29]), "+f"(d[30]), "+f"(d[31]), "+f"(d[32]), "+f"(d[33]), "+f"(d[34]), "+f"(d[35]), "+f"(d[36]), "+f"(d[37]), "+f"(d[38]), "+f"(d[39]), "+f"(d[40]), "+f"(d[41]), "+f"(d[42]), "+f"(d[43]), "+f"(d[44]), "+f"(d[45]), "+f"(d[46]), "+f"(d[47]), "+f"(d[48]), "+f"(d[49]), "+f"(d[50]), "+f"(d[51]), "+f"(d[52]), "+f"(d[53]), "+f"(d[54]), "+f"(d[55]), "+f"(d[56]), "+f"(d[57]), "+f"(d[58]), "+f"(d[59]), "+f"(d[60]), "+f"(d[61]), "+f"(d[62]), "+f"(d[63]), "+f"(d[64]), "+f"(d[65]), "+f"(d[66]), "+f"(d[67]), "+f"(d[68]), "+f"(d[69]), "+f"(d[70]), "+f"(d[71]), "+f"(d[72]), "+f"(d[73]), "+f"(d[74]), "+f"(d[75]), "+f"(d[76]), "+f"(d[77]), "+f"(d[78]), "+f"(d[79]), "+f"(d[80]), "+f"(d[81]), "+f"(d[82]), "+f"(d[83]), "+f"(d[84]), "+f"(d[85]), "+f"(d[86]), "+f"(d[87]), "+f"(d[88]), "+f"(d[89]), "+f"(d[90]), "+f"(d[91]), "+f"(d[92]), "+f"(d[93]), "+f"(d[94]), "+f"(d[95])
    : "l"(da), "l"(db), "r"(scale_d), "n"(TNSPB));
}
template <int TNSPB>
__device__ __forceinline__ void wgmma_ss_n224(float (&d)[112], uint64_t da, uint64_t db, int scale_d) {
  asm volatile("{\n.reg .pred p;\nsetp.ne.b32 p, %114, 0;\n"
    "wgmma.mma_async.sync.aligned.m64n224k16.f32.bf16.bf16 {%0, %1, %2, %3, %4, %5, %6, %7, %8, %9, %10, %11, %12, %13, %14, %15, %16, %17, %18, %19, %20, %21, %22, %23, %24, %25, %26, %27, %28, %29, %30, %31, %32, %33, %34, %35, %36, %37, %38, %39, %40, %41, %42, %43, %44, %45, %46, %47, %48, %49, %50, %51, %52, %53, %54, %55, %56, %57, %58, %59, %60, %61, %62, %63, %64, %65, %66, %67, %68, %69, %70, %71, %72, %73, %74, %75, %76, %77, %78, %79, %80, %81, %82, %83, %84, %85, %86, %87, %88, %89, %90, %91, %92, %93, %94, %95, %96, %97, %98, %99, %100, %101, %102, %103, %104, %105, %106, %107, %108, %109, %110, %111}, %112, %113, p, 1, 1, 0, %115;\n}"
    : "+f"(d[0]), "+f"(d[1]), "+f"(d[2]), "+f"(d[3]), "+f"(d[4]), "+f"(d[5]), "+f"(d[6]), "+f"(d[7]), "+f"(d[8]), "+f"(d[9]), "+f"(d[10]), "+f"(d[11]), "+f"(d[12]), "+f"(d[13]), "+f"(d[14]), "+f"(d[15]), "+f"(d[16]), "+f"(d[17]), "+f"(d[18]), "+f"(d[19]), "+f"(d[20]), "+f"(d[21]), "+f"(d[22]), "+f"(d[23]), "+f"(d[24]), "+f"(d[25]), "+f"(d[26]), "+f"(d[27]), "+f"(d[28]), "+f"(d[29]), "+f"(d[30]), "+f"(d[31]), "+f"(d[32]), "+f"(d[33]), "+f"(d[34]), "+f"(d[35]), "+f"(d[36]), "+f"(d[37]), "+f"(d[38]), "+f"(d[39]), "+f"(d[40]), "+f"(d[41]), "+f"(d[42]), "+f"(d[43]), "+f"(d[44]), "+f"(d[45]), "+f"(d[46]), "+f"(d[47]), "+f"(d[48]), "+f"(d[49]), "+f"(d[50]), "+f"(d[51]), "+f"(d[52]), "+f"(d[53]), "+f"(d[54]), "+f"(d[55]), "+f"(d[56]), "+f"(d[57]), "+f"(d[58]), "+f"(d[59]), "+f"(d[60]), "+f"(d[61]), "+f"(d[62]), "+f"(d[63]), "+f"(d[64]), "+f"(d[65]), "+f"(d[66]), "+f"(d[67]), "+f"(d[68]), "+f"(d[69]), "+f"(d[70]), "+f"(d[71]), "+f"(d[72]), "+f"(d[73]), "+f"(d[74]), "+f"(d[75]), "+f"(d[76]), "+f"(d[77]), "+f"(d[78]), "+f"(d[79]), "+f"(d[80]), "+f"(d[81]), "+f"(d[82]), "+f"(d[83]), "+f"(d[84]), "+f"(d[85]), "+f"(d[86]), "+f"(d[87]), "+f"(d[88]), "+f"(d[89]), "+f"(d[90]), "+f"(d[91]), "+f"(d[92]), "+f"(d[93]), "+f"(d[94]), "+f"(d[95]), "+f"(d[96]), "+f"(d[97]), "+f"(d[98]), "+f"(d[99]), "+f"(d[100]), "+f"(d[101]), "+f"(d[102]), "+f"(d[103]), "+f"(d[104]), "+f"(d[105]), "+f"(d[106]), "+f"(d[107]), "+f"(d[108]), "+f"(d[109]), "+f"(d[110]), "+f"(d[111])
    : "l"(da), "l"(db), "r"(scale_d), "n"(TNSPB));
}
template <int TNSPB>
__device__ __forceinline__ void wgmma_rs_n64(float (&d)[32], uint32_t a0, uint32_t a1, uint32_t a2, uint32_t a3, uint64_t db, int scale_d) {
  asm volatile("{\n.reg .pred p;\nsetp.ne.b32 p, %37, 0;\n"
    "wgmma.mma_async.sync.aligned.m64n64k16.f32.bf16.bf16 {%0, %1, %2, %3, %4, %5, %6, %7, %8, %9, %10, %11, %12, %13, %14, %15, %16, %17, %18, %19, %20, %21, %22, %23, %24, %25, %26, %27, %28, %29, %30, %31}, {%32, %33, %34, %35}, %36, p, 1, 1, %38;\n}"
    : "+f"(d[0]), "+f"(d[1]), "+f"(d[2]), "+f"(d[3]), "+f"(d[4]), "+f"(d[5]), "+f"(d[6]), "+f"(d[7]), "+f"(d[8]), "+f"(d[9]), "+f"(d[10]), "+f"(d[11]), "+f"(d[12]), "+f"(d[13]), "+f"(d[14]), "+f"(d[15]), "+f"(d[16]), "+f"(d[17]), "+f"(d[18]), "+f"(d[19]), "+f"(d[20]), "+f"(d[21]), "+f"(d[22]), "+f"(d[23]), "+f"(d[24]), "+f"(d[25]), "+f"(d[26]), "+f"(d[27]), "+f"(d[28]), "+f"(d[29]), "+f"(d[30]), "+f"(d[31])
    : "r"(a0), "r"(a1), "r"(a2), "r"(a3), "l"(db), "r"(scale_d), "n"(TNSPB));
}
template <int TNSPB>
__device__ __forceinline__ void wgmma_rs_n32(float (&d)[16], uint32_t a0, uint32_t a1, uint32_t a2, uint32_t a3, uint64_t db, int scale_d) {
  asm volatile("{\n.reg .pred p;\nsetp.ne.b32 p, %21, 0;\n"
    "wgmma.mma_async.sync.aligned.m64n32k16.f32.bf16.bf16 {%0, %1, %2, %3, %4, %5, %6, %7, %8, %9, %10, %11, %12, %13, %14, %15}, {%16, %17, %18, %19}, %20, p, 1, 1, %22;\n}"
    : "+f"(d[0]), "+f"(d[1]), "+f"(d[2]), "+f"(d[3]), "+f"(d[4]), "+f"(d[5]), "+f"(d[6]), "+f"(d[7]), "+f"(d[8]), "+f"(d[9]), "+f"(d[10]), "+f"(d[11]), "+f"(d[12]), "+f"(d[13]), "+f"(d[14]), "+f"(d[15])
    : "r"(a0), "r"(a1), "r"(a2), "r"(a3), "l"(db), "r"(scale_d), "n"(TNSPB));
}
template <int N, int TNSPB> __device__ __forceinline__ void wgmma_ss(float (&d)[N/2], uint64_t da, uint64_t db, int scale_d) {
  if constexpr (N == 128) wgmma_ss_n128<TNSPB>(d, da, db, scale_d);
  if constexpr (N == 192) wgmma_ss_n192<TNSPB>(d, da, db, scale_d);
  if constexpr (N == 224) wgmma_ss_n224<TNSPB>(d, da, db, scale_d);
}
template <int N, int TNSPB> __device__ __forceinline__ void wgmma_rs(float (&d)[N/2], uint32_t a0, uint32_t a1, uint32_t a2, uint32_t a3, uint64_t db, int scale_d) {
  if constexpr (N == 64) wgmma_rs_n64<TNSPB>(d, a0, a1, a2, a3, db, scale_d);
  if constexpr (N == 32) wgmma_rs_n32<TNSPB>(d, a0, a1, a2, a3, db, scale_d);
}

constexpr int SEQ = 2048, DM = 1024, NH = 32, DH = 32, DFF = 3584;

__device__ __align__(1024) bf16 g_qkv[SEQ * 3 * DM];
__device__ __align__(1024) bf16 g_o[SEQ * DM];
__device__ __align__(1024) bf16 g_h[SEQ * DM];
__device__ __align__(1024) bf16 g_h1[SEQ * DFF];
__device__ float2 g_ln1[SEQ];
__device__ float g_cs1[24 * 3 * DM];
__device__ float g_cs2[DFF];
__device__ float2 g_ln2[SEQ * 8];
__device__ unsigned g_cnt[32];

#define TL_START(k) do {} while (0)
#define TL_END(k) do {} while (0)

enum { EPI_QKV = 0, EPI_OPROJ = 1, EPI_FFN1 = 2, EPI_FFN2 = 3 };
template <int EPI> struct GCfg;
template <> struct GCfg<EPI_QKV>   { static constexpr int BM = 256, BN = 192, ST = 4, CH = 64, NT = 1, KB = 16, RBUF = 0; };
template <> struct GCfg<EPI_OPROJ> { static constexpr int BM = 128, BN = 128, ST = 5, CH = 64, NT = 1, KB = 16, RBUF = 1; };
template <> struct GCfg<EPI_FFN1>  { static constexpr int BM = 128, BN = 224, ST = 4, CH = 32, NT = 2, KB = 16, RBUF = 0; };
template <> struct GCfg<EPI_FFN2>  { static constexpr int BM = 128, BN = 128, ST = 5, CH = 64, NT = 1, KB = 56, RBUF = 1; };

template <int EPI> struct GLay {
  using C = GCfg<EPI>;
  static constexpr uint32_t A_BYTES = C::BM * 128, B_BYTES = C::BN * 128, STAGE = A_BYTES + B_BYTES;
  static constexpr uint32_t R_OFF = C::ST * STAGE;
  static constexpr uint32_t R_BYTES = C::RBUF ? C::BM * C::BN * 2 : 0;
  static constexpr uint32_t BAR_OFF = R_OFF + R_BYTES;
  static constexpr uint32_t AUX_OFF = BAR_OFF + 128;
  static_assert(8 * (2 * C::ST + 2) <= 128, "barrier area");
  static constexpr uint32_t AUX_BYTES = (EPI == EPI_QKV) ? 192 * 4 : (EPI == EPI_FFN1) ? (128 * 8 + 448 * 8) : 0;
  static constexpr uint32_t TOTAL = AUX_OFF + AUX_BYTES + 1024;
};

__device__ __forceinline__ void qkv_aux(const bf16* __restrict__ x, const bf16* __restrict__ w, float* colp_s,
                                        uint32_t epi_bar) {
  const int at = threadIdx.x - 32, aw = at >> 5, lane = at & 31;
  const int mb = blockIdx.y, nb = blockIdx.x, n0 = nb * 192;
  for (int i = aw; i < 16; i += 3) {
    const int row = mb * 256 + nb * 16 + i;
    const uint4* p = reinterpret_cast<const uint4*>(x + (size_t)row * DM) + lane;
    uint4 v[4];
#pragma unroll
    for (int q = 0; q < 4; q++) v[q] = __ldg(p + q * 32);
    float s = 0.f;
#pragma unroll
    for (int q = 0; q < 4; q++)
      s += (bf_lo(v[q].x) + bf_hi(v[q].x)) + (bf_lo(v[q].y) + bf_hi(v[q].y)) + (bf_lo(v[q].z) + bf_hi(v[q].z)) +
           (bf_lo(v[q].w) + bf_hi(v[q].w));
    const float mean = warp_sum(s) * (1.0f / DM);
    float ss = 0.f;
#pragma unroll
    for (int q = 0; q < 4; q++) {
      const uint32_t u[4] = {v[q].x, v[q].y, v[q].z, v[q].w};
#pragma unroll
      for (int e = 0; e < 4; e++) {
        const float a = bf_lo(u[e]) - mean, b = bf_hi(u[e]) - mean;
        ss = fmaf(a, a, ss); ss = fmaf(b, b, ss);
      }
    }
    const float var = warp_sum(ss) * (1.0f / DM);
    const float rstd = 1.0f / sqrtf(var + 1e-5f);
    if (lane == 0) g_ln1[row] = make_float2(rstd, -mean * rstd);
  }
  {
    float c[6] = {0.f, 0.f, 0.f, 0.f, 0.f, 0.f};
    const uint32_t* wp = reinterpret_cast<const uint32_t*>(w + (size_t)(mb * 128) * (3 * DM) + n0) + lane;
#pragma unroll 4
    for (int kk = aw; kk < 128; kk += 3) {
      const uint32_t* r = wp + (size_t)kk * (3 * DM / 2);
      const uint32_t a0 = __ldg(r), a1 = __ldg(r + 32), a2 = __ldg(r + 64);
      c[0] += bf_lo(a0); c[1] += bf_hi(a0); c[2] += bf_lo(a1); c[3] += bf_hi(a1); c[4] += bf_lo(a2); c[5] += bf_hi(a2);
    }
    float2* dst = reinterpret_cast<float2*>(g_cs1 + (size_t)(mb * 3 + aw) * (3 * DM) + n0) + lane;
    dst[0] = make_float2(c[0], c[1]); dst[32] = make_float2(c[2], c[3]); dst[64] = make_float2(c[4], c[5]);
  }
  __threadfence();
  __syncwarp();
  if (lane == 0) { atomicAdd(&g_cnt[mb], 1u); atomicAdd(&g_cnt[8 + nb], 1u); }
  if (lane == 0) {
    int n = 0;
    while (ld_acquire(&g_cnt[mb]) < 48u || ld_acquire(&g_cnt[8 + nb]) < 24u) {
      __nanosleep(64);
    }
    (void)n;
  }
  __syncwarp();
  {
    float2 acc = make_float2(0.f, 0.f);
    const float2* src = reinterpret_cast<const float2*>(g_cs1 + n0) + at;
#pragma unroll 8
    for (int p = 0; p < 24; p++) {
      const float2 v = __ldcg(src + (size_t)p * (3 * DM / 2));
      acc.x += v.x; acc.y += v.y;
    }
    reinterpret_cast<float2*>(colp_s)[at] = acc;
  }
  mbar_arrive(epi_bar);
}

__device__ __forceinline__ void ffn1_aux(const bf16* __restrict__ b1, float2* rowp_s, float2* colp_s, int m0, int n0,
                                         uint32_t epi_bar) {
  const int at = threadIdx.x - 32;
  griddep_wait();
  for (int r = at; r < 128; r += 96) {
    const float4* p = reinterpret_cast<const float4*>(g_ln2 + (size_t)(m0 + r) * 8);
    float4 v[4];
#pragma unroll
    for (int q = 0; q < 4; q++) v[q] = __ldcg(p + q);
    float mean = 0.f, m2 = 0.f;
#pragma unroll
    for (int q = 0; q < 4; q++) { mean += v[q].x + v[q].z; m2 += v[q].y + v[q].w; }
    mean *= 0.125f;
#pragma unroll
    for (int q = 0; q < 4; q++) {
      const float a = v[q].x - mean, b = v[q].z - mean;
      m2 = fmaf(128.f * a, a, m2); m2 = fmaf(128.f * b, b, m2);
    }
    const float rstd = 1.0f / sqrtf(m2 * (1.0f / DM) + 1e-5f);
    rowp_s[r] = make_float2(rstd, -mean * rstd);
  }
  for (int c = at; c < 448; c += 96) colp_s[c] = make_float2(__ldcg(&g_cs2[n0 + c]), __bfloat162float(b1[n0 + c]));
  mbar_arrive(epi_bar);
}

__device__ __forceinline__ float gelu_tanh(float t) {
  const float u = t * fmaf(t * t, 0.7978845608028654f * 0.044715f, 0.7978845608028654f);
  const float h = 0.5f * t;
  return fmaf(h, tanh_approx(u), h);
}

template <int EPI>
__global__ void __launch_bounds__(384, 1)
gemm_kernel(const __grid_constant__ CUtensorMap tmA, const __grid_constant__ CUtensorMap tmB,
            const __grid_constant__ CUtensorMap tmR, const __grid_constant__ CUtensorMap tmC,
            const bf16* __restrict__ px, const bf16* __restrict__ pw, const bf16* __restrict__ pbias) {
  using C = GCfg<EPI>;
  using L = GLay<EPI>;
  constexpr int BM = C::BM, BN = C::BN, ST = C::ST, CH = C::CH, NT = C::NT, KB = C::KB;
  constexpr int MI = BM / 128;
  constexpr int SWZ = (CH == 64) ? 1 : 2;
  constexpr int CB = CH * 2;
  constexpr int CPC = CH / 8;
  static_assert(C::RBUF || (KB % ST == 0 && 2 * L::STAGE >= BM * BN * 2), "borrowed staging");
  extern __shared__ uint8_t smem_raw[];
  const uint32_t sbase = (smem_u32(smem_raw) + 1023u) & ~1023u;
  const uint32_t bar_base = sbase + L::BAR_OFF;
  auto full_bar = [&](int s) { return bar_base + 8u * s; };
  auto empty_bar = [&](int s) { return bar_base + 8u * (ST + s); };
  const uint32_t epi_bar = bar_base + 8u * (2 * ST), res_bar = epi_bar + 8u;
  uint8_t* aux_s = smem_raw + (sbase - smem_u32(smem_raw)) + L::AUX_OFF;

  const int warp = threadIdx.x >> 5, lane = threadIdx.x & 31;
  const int m0 = blockIdx.y * BM, n0 = blockIdx.x * (BN * NT);
  TL_START(EPI == EPI_QKV ? 0 : EPI + 1);

  if (threadIdx.x == 0) {
    for (int s = 0; s < ST; s++) { mbar_init(full_bar(s), 1); mbar_init(empty_bar(s), 2); }
    mbar_init(epi_bar, 96);
    mbar_init(res_bar, 1);
    fence_mbar_init();
    prefetch_tmap(&tmA); prefetch_tmap(&tmB); prefetch_tmap(&tmC);
    if (C::RBUF) prefetch_tmap(&tmR);
  }
  __syncthreads();
  griddep_launch();

  if (warp < 4) {
    reg_dealloc<40>();
    if (warp == 0) {
      if (lane == 0) {
        for (int s = 0; s < ST; s++) {
          mbar_expect_tx(full_bar(s), L::STAGE);
          tma_load_3d(sbase + s * L::STAGE + L::A_BYTES, &tmB, 0, s * 64, n0 / CH, full_bar(s));
        }
        griddep_wait();
        for (int s = 0; s < ST; s++) tma_load_2d(sbase + s * L::STAGE, &tmA, s * 64, m0, full_bar(s));
        if (C::RBUF) {
          mbar_expect_tx(res_bar, L::R_BYTES);
#pragma unroll
          for (int c = 0; c < BN / 64; c++)
#pragma unroll
            for (int w = 0; w < BM / 64; w++)
              tma_load_2d(sbase + L::R_OFF + c * (BM * 128) + w * (64 * 128), &tmR, n0 + c * 64, m0 + w * 64, res_bar);
        }
        int s = 0; uint32_t ph = 1;
        for (int it = ST; it < NT * KB; it++) {
          const int tile = it / KB, kb = it % KB;
          mbar_wait(empty_bar(s), ph ^ 1);
          mbar_expect_tx(full_bar(s), L::STAGE);
          tma_load_2d(sbase + s * L::STAGE, &tmA, kb * 64, m0, full_bar(s));
          tma_load_3d(sbase + s * L::STAGE + L::A_BYTES, &tmB, 0, kb * 64, (n0 + tile * BN) / CH, full_bar(s));
          if (++s == ST) { s = 0; ph ^= 1; }
        }
      }
    } else {
      if constexpr (EPI == EPI_QKV) qkv_aux(px, pw, reinterpret_cast<float*>(aux_s), epi_bar);
      if constexpr (EPI == EPI_FFN1)
        ffn1_aux(pbias, reinterpret_cast<float2*>(aux_s), reinterpret_cast<float2*>(aux_s + 128 * 8), m0, n0, epi_bar);
    }
  } else {
    reg_alloc<232>();
    const int wgc = (warp >> 2) - 1, w4 = warp & 3;
    const int t = threadIdx.x & 127;
    const int q2 = (lane & 3) * 2;
    uint32_t bias2[(EPI == EPI_FFN2) ? BN / 8 : 1];
    if constexpr (EPI == EPI_FFN2) {
#pragma unroll
      for (int g = 0; g < BN / 8; g++) bias2[g] = __ldg(reinterpret_cast<const uint32_t*>(pbias + n0 + g * 8 + q2));
    }
    int s = 0; uint32_t ph = 0;
    for (int tile = 0; tile < NT; tile++) {
      float acc[MI][BN / 2];
      int prev_s = 0;
      for (int kb = 0; kb < KB; kb++) {
        mbar_wait(full_bar(s), ph);
        const uint32_t sa = sbase + s * L::STAGE, sb = sa + L::A_BYTES;
        wgmma_fence();
#pragma unroll
        for (int k16 = 0; k16 < 4; k16++) {
          const uint64_t db = make_desc(sb + k16 * (16 * CB), 64 * CB, 8 * CB, SWZ);
#pragma unroll
          for (int mi = 0; mi < MI; mi++) {
            const uint64_t da = make_desc(sa + (wgc * (BM / 2) + mi * 64) * 128 + k16 * 32, 16, 1024, 1);
            wgmma_ss<BN, 1>(acc[mi], da, db, (kb | k16) != 0);
          }
        }
        wgmma_commit();
        wgmma_wait<1>();
        if (kb > 0 && (C::RBUF || kb < KB - 1) && t == 0) mbar_arrive(empty_bar(prev_s));
        prev_s = s;
        if (++s == ST) { s = 0; ph ^= 1; }
      }
      wgmma_wait<0>();
      uint32_t stg;
      if constexpr (C::RBUF) {
        stg = sbase + L::R_OFF;
        mbar_wait(res_bar, 0);
      } else {
        stg = sbase + (ST - 2) * L::STAGE;
        named_bar_sync(1, 256);
        if (tile == 0) mbar_wait(epi_bar, 0);
      }
      const int nt0 = n0 + tile * BN;
#pragma unroll
      for (int mi = 0; mi < MI; mi++) {
        const int rl0 = wgc * (BM / 2) + mi * 64 + w4 * 16 + (lane >> 2);
        const int rs = wgc * (BM / 2) + mi * 64 + w4 * 16 + (lane & 7) + ((lane >> 3) & 1) * 8;
        const int rsw = (CH == 64) ? (rs & 7) : ((rs >> 1) & 3);
        float2 rp0, rp1;
        if constexpr (EPI == EPI_QKV) { rp0 = __ldcg(&g_ln1[m0 + rl0]); rp1 = __ldcg(&g_ln1[m0 + rl0 + 8]); }
        if constexpr (EPI == EPI_FFN1) {
          rp0 = reinterpret_cast<const float2*>(aux_s)[rl0]; rp1 = reinterpret_cast<const float2*>(aux_s)[rl0 + 8];
        }
#pragma unroll
        for (int jj = 0; jj < BN / 16; jj++) {
          float* d = &acc[mi][jj * 8];
          const int cg = 2 * jj + (lane >> 4);
          const uint32_t addr = stg + (cg / CPC) * (BM * CB) + rs * CB + (((cg % CPC) ^ rsw) << 4);
          uint32_t p0, p1, p2, p3;
          if constexpr (EPI == EPI_QKV) {
            const float* colp = reinterpret_cast<const float*>(aux_s);
            const float2 ca = *reinterpret_cast<const float2*>(colp + jj * 16 + q2);
            const float2 cb = *reinterpret_cast<const float2*>(colp + jj * 16 + 8 + q2);
            p0 = pack_bf16(fmaf(d[0], rp0.x, rp0.y * ca.x), fmaf(d[1], rp0.x, rp0.y * ca.y));
            p1 = pack_bf16(fmaf(d[2], rp1.x, rp1.y * ca.x), fmaf(d[3], rp1.x, rp1.y * ca.y));
            p2 = pack_bf16(fmaf(d[4], rp0.x, rp0.y * cb.x), fmaf(d[5], rp0.x, rp0.y * cb.y));
            p3 = pack_bf16(fmaf(d[6], rp1.x, rp1.y * cb.x), fmaf(d[7], rp1.x, rp1.y * cb.y));
          } else if constexpr (EPI == EPI_FFN1) {
            const float2* colp = reinterpret_cast<const float2*>(aux_s + 128 * 8) + tile * BN;
            const float4 ca = *reinterpret_cast<const float4*>(colp + jj * 16 + q2);
            const float4 cb = *reinterpret_cast<const float4*>(colp + jj * 16 + 8 + q2);
            p0 = pack_bf16(gelu_tanh(fmaf(d[0], rp0.x, fmaf(rp0.y, ca.x, ca.y))), gelu_tanh(fmaf(d[1], rp0.x, fmaf(rp0.y, ca.z, ca.w))));
            p1 = pack_bf16(gelu_tanh(fmaf(d[2], rp1.x, fmaf(rp1.y, ca.x, ca.y))), gelu_tanh(fmaf(d[3], rp1.x, fmaf(rp1.y, ca.z, ca.w))));
            p2 = pack_bf16(gelu_tanh(fmaf(d[4], rp0.x, fmaf(rp0.y, cb.x, cb.y))), gelu_tanh(fmaf(d[5], rp0.x, fmaf(rp0.y, cb.z, cb.w))));
            p3 = pack_bf16(gelu_tanh(fmaf(d[6], rp1.x, fmaf(rp1.y, cb.x, cb.y))), gelu_tanh(fmaf(d[7], rp1.x, fmaf(rp1.y, cb.z, cb.w))));
          } else {
            uint32_t r0, r1, r2, r3;
            ldmatrix_x4(addr, r0, r1, r2, r3);
            float b0 = 0.f, b1 = 0.f, b2 = 0.f, b3 = 0.f;
            if constexpr (EPI == EPI_FFN2) {
              b0 = bf_lo(bias2[2 * jj]); b1 = bf_hi(bias2[2 * jj]); b2 = bf_lo(bias2[2 * jj + 1]); b3 = bf_hi(bias2[2 * jj + 1]);
            }
            p0 = pack_bf16(d[0] + b0 + bf_lo(r0), d[1] + b1 + bf_hi(r0));
            p1 = pack_bf16(d[2] + b0 + bf_lo(r1), d[3] + b1 + bf_hi(r1));
            p2 = pack_bf16(d[4] + b2 + bf_lo(r2), d[5] + b3 + bf_hi(r2));
            p3 = pack_bf16(d[6] + b2 + bf_lo(r3), d[7] + b3 + bf_hi(r3));
            if constexpr (EPI == EPI_OPROJ) {
              d[0] = bf_lo(p0); d[1] = bf_hi(p0); d[2] = bf_lo(p1); d[3] = bf_hi(p1);
              d[4] = bf_lo(p2); d[5] = bf_hi(p2); d[6] = bf_lo(p3); d[7] = bf_hi(p3);
            }
          }
          stmatrix_x4(addr, p0, p1, p2, p3);
        }
        if constexpr (EPI == EPI_OPROJ) {
          float s0 = 0.f, s1 = 0.f;
#pragma unroll
          for (int jj = 0; jj < BN / 16; jj++) {
            const float* d = &acc[mi][jj * 8];
            s0 += (d[0] + d[1]) + (d[4] + d[5]); s1 += (d[2] + d[3]) + (d[6] + d[7]);
          }
          s0 += __shfl_xor_sync(0xffffffffu, s0, 1); s0 += __shfl_xor_sync(0xffffffffu, s0, 2);
          s1 += __shfl_xor_sync(0xffffffffu, s1, 1); s1 += __shfl_xor_sync(0xffffffffu, s1, 2);
          const float mu0 = s0 * (1.0f / BN), mu1 = s1 * (1.0f / BN);
          float v0 = 0.f, v1 = 0.f;
#pragma unroll
          for (int jj = 0; jj < BN / 16; jj++) {
            const float* d = &acc[mi][jj * 8];
            float a;
            a = d[0] - mu0; v0 = fmaf(a, a, v0); a = d[1] - mu0; v0 = fmaf(a, a, v0);
            a = d[4] - mu0; v0 = fmaf(a, a, v0); a = d[5] - mu0; v0 = fmaf(a, a, v0);
            a = d[2] - mu1; v1 = fmaf(a, a, v1); a = d[3] - mu1; v1 = fmaf(a, a, v1);
            a = d[6] - mu1; v1 = fmaf(a, a, v1); a = d[7] - mu1; v1 = fmaf(a, a, v1);
          }
          v0 += __shfl_xor_sync(0xffffffffu, v0, 1); v0 += __shfl_xor_sync(0xffffffffu, v0, 2);
          v1 += __shfl_xor_sync(0xffffffffu, v1, 1); v1 += __shfl_xor_sync(0xffffffffu, v1, 2);
          if ((lane & 3) == 0) {
            g_ln2[(size_t)(m0 + rl0) * 8 + blockIdx.x] = make_float2(mu0, v0);
            g_ln2[(size_t)(m0 + rl0 + 8) * 8 + blockIdx.x] = make_float2(mu1, v1);
          }
        }
      }
      fence_proxy_async();
      named_bar_sync(2 + wgc, 128);
      if (t == 0) {
#pragma unroll
        for (int c = 0; c < BN / CH; c++)
          tma_store_2d(&tmC, stg + c * (BM * CB) + wgc * (BM / 2) * CB, nt0 + c * CH, m0 + wgc * (BM / 2));
        tma_store_commit();
        tma_store_wait_read<0>();
        if constexpr (!C::RBUF) { mbar_arrive(empty_bar(ST - 2)); mbar_arrive(empty_bar(ST - 1)); }
      }
    }
    if (t == 0) TL_END(EPI == EPI_QKV ? 0 : EPI + 1);
  }
}

constexpr int AT_ST = 6;
constexpr uint32_t AT_SMEM = AT_ST * 16384 + 8 * 2 * AT_ST + 1024;

__global__ void __launch_bounds__(640, 1)
attn_kernel(const __grid_constant__ CUtensorMap tmKV, const bf16* __restrict__ w1) {
  extern __shared__ uint8_t smem_raw[];
  const uint32_t sbase = (smem_u32(smem_raw) + 1023u) & ~1023u;
  const uint32_t bar_base = sbase + AT_ST * 16384;
  auto full_bar = [&](int s) { return bar_base + 8u * s; };
  auto empty_bar = [&](int s) { return bar_base + 8u * (AT_ST + s); };
  const int warp = threadIdx.x >> 5, lane = threadIdx.x & 31;
  const int head = blockIdx.x >> 2, qb = blockIdx.x & 3;
  TL_START(1);

  if (threadIdx.x == 0) {
    for (int s = 0; s < AT_ST; s++) { mbar_init(full_bar(s), 1); mbar_init(empty_bar(s), 4); }
    fence_mbar_init();
    prefetch_tmap(&tmKV);
  }
  __syncthreads();
  griddep_launch();

  if (warp < 4) {
    reg_dealloc<24>();
    if (warp == 0) {
      if (lane == 0) {
        griddep_wait();
        int s = 0; uint32_t ph = 0;
        for (int it = 0; it < 32; it++) {
          mbar_wait(empty_bar(s), ph ^ 1);
          mbar_expect_tx(full_bar(s), 16384);
          tma_load_2d(sbase + s * 16384, &tmKV, DM + head * DH, (it & 15) * 128, full_bar(s));
          tma_load_2d(sbase + s * 16384 + 8192, &tmKV, 2 * DM + head * DH, (it & 15) * 128, full_bar(s));
          if (++s == AT_ST) { s = 0; ph ^= 1; }
        }
      }
    } else if (warp == 1) {
      if (blockIdx.x < DFF / 32) {
        float cs[8];
#pragma unroll
        for (int i = 0; i < 8; i++) cs[i] = 0.f;
        const uint4* wp = reinterpret_cast<const uint4*>(w1 + (size_t)(lane >> 2) * DFF + blockIdx.x * 32 + (lane & 3) * 8);
#pragma unroll 4
        for (int i = 0; i < DM / 8; i++) {
          const uint4 v = __ldg(wp + (size_t)i * (8 * DFF / 8));
          cs[0] += bf_lo(v.x); cs[1] += bf_hi(v.x); cs[2] += bf_lo(v.y); cs[3] += bf_hi(v.y);
          cs[4] += bf_lo(v.z); cs[5] += bf_hi(v.z); cs[6] += bf_lo(v.w); cs[7] += bf_hi(v.w);
        }
#pragma unroll
        for (int i = 0; i < 8; i++) {
          cs[i] += __shfl_xor_sync(0xffffffffu, cs[i], 4);
          cs[i] += __shfl_xor_sync(0xffffffffu, cs[i], 8);
          cs[i] += __shfl_xor_sync(0xffffffffu, cs[i], 16);
        }
        if (lane < 4) {
          float4* dst = reinterpret_cast<float4*>(&g_cs2[blockIdx.x * 32 + lane * 8]);
          dst[0] = make_float4(cs[0], cs[1], cs[2], cs[3]);
          dst[1] = make_float4(cs[4], cs[5], cs[6], cs[7]);
        }
      }
    } else if (warp == 2) {
      griddep_wait();
      if (blockIdx.x == 0) g_cnt[lane] = 0u;
    }
  } else {
    reg_alloc<112>();
    const int wg = (warp >> 2) - 1, w4 = warp & 3;
    const int t = threadIdx.x & 127;
    const float SC = 0.17677669529663687f * 1.4426950408889634f;
    griddep_wait();
    int s = 0; uint32_t ph = 0;
    for (int pass = 0; pass < 2; pass++) {
      const int row0 = qb * 512 + pass * 256 + wg * 64 + w4 * 16 + (lane >> 2);
      const uint32_t* qp = reinterpret_cast<const uint32_t*>(g_qkv + (size_t)row0 * (3 * DM) + head * DH + (lane & 3) * 2);
      uint32_t q[8];
      q[0] = __ldcg(qp);     q[1] = __ldcg(qp + 8 * (3 * DM / 2));     q[2] = __ldcg(qp + 4);  q[3] = __ldcg(qp + 8 * (3 * DM / 2) + 4);
      q[4] = __ldcg(qp + 8); q[5] = __ldcg(qp + 8 * (3 * DM / 2) + 8); q[6] = __ldcg(qp + 12); q[7] = __ldcg(qp + 8 * (3 * DM / 2) + 12);
      float m0 = -INFINITY, m1 = -INFINITY, l0 = 0.f, l1 = 0.f;
      float oacc[16];
#pragma unroll
      for (int i = 0; i < 16; i++) oacc[i] = 0.f;
      int prev_s = 0;
      for (int j = 0; j < 32; j++) {
        const int half = j & 1;
        if (half == 0) mbar_wait(full_bar(s), ph);
        const uint32_t sk = sbase + s * 16384 + half * 4096, sv = sk + 8192;
        float sc[32];
        wgmma_fence();
        wgmma_rs<64, 0>(sc, q[0], q[1], q[2], q[3], make_desc(sk, 16, 512, 2), 0);
        wgmma_rs<64, 0>(sc, q[4], q[5], q[6], q[7], make_desc(sk + 32, 16, 512, 2), 1);
        wgmma_commit();
        wgmma_wait<0>();
        if (half == 0 && j > 0 && t == 0) mbar_arrive(empty_bar(prev_s));
        float mx0 = fmaxf(sc[0], sc[1]), mx1 = fmaxf(sc[2], sc[3]);
#pragma unroll
        for (int g = 1; g < 8; g++) {
          mx0 = fmaxf(mx0, fmaxf(sc[4 * g], sc[4 * g + 1]));
          mx1 = fmaxf(mx1, fmaxf(sc[4 * g + 2], sc[4 * g + 3]));
        }
        mx0 = fmaxf(mx0, __shfl_xor_sync(0xffffffffu, mx0, 1)); mx0 = fmaxf(mx0, __shfl_xor_sync(0xffffffffu, mx0, 2));
        mx1 = fmaxf(mx1, __shfl_xor_sync(0xffffffffu, mx1, 1)); mx1 = fmaxf(mx1, __shfl_xor_sync(0xffffffffu, mx1, 2));
        const float mn0 = fmaxf(m0, mx0), mn1 = fmaxf(m1, mx1);
        const float a0 = ex2_approx((m0 - mn0) * SC), a1 = ex2_approx((m1 - mn1) * SC);
        m0 = mn0; m1 = mn1;
        const float mc0 = mn0 * SC, mc1 = mn1 * SC;
        uint32_t p[16];
        float s0a = 0.f, s0b = 0.f, s1a = 0.f, s1b = 0.f;
#pragma unroll
        for (int g = 0; g < 8; g++) {
          const float e0 = ex2_approx(fmaf(sc[4 * g], SC, -mc0)), e1 = ex2_approx(fmaf(sc[4 * g + 1], SC, -mc0));
          const float e2 = ex2_approx(fmaf(sc[4 * g + 2], SC, -mc1)), e3 = ex2_approx(fmaf(sc[4 * g + 3], SC, -mc1));
          s0a += e0; s0b += e1; s1a += e2; s1b += e3;
          p[2 * g] = pack_bf16(e0, e1);
          p[2 * g + 1] = pack_bf16(e2, e3);
        }
        l0 = fmaf(l0, a0, s0a + s0b); l1 = fmaf(l1, a1, s1a + s1b);
#pragma unroll
        for (int g = 0; g < 4; g++) {
          oacc[4 * g] *= a0; oacc[4 * g + 1] *= a0; oacc[4 * g + 2] *= a1; oacc[4 * g + 3] *= a1;
        }
        wgmma_fence();
#pragma unroll
        for (int k = 0; k < 4; k++)
          wgmma_rs<32, 1>(oacc, p[4 * k], p[4 * k + 1], p[4 * k + 2], p[4 * k + 3], make_desc(sv + k * 1024, 16, 512, 2), 1);
        wgmma_commit();
        if (half == 1) {
          prev_s = s;
          if (++s == AT_ST) { s = 0; ph ^= 1; }
        }
      }
      wgmma_wait<0>();
      if (t == 0) mbar_arrive(empty_bar(prev_s));
      l0 += __shfl_xor_sync(0xffffffffu, l0, 1); l0 += __shfl_xor_sync(0xffffffffu, l0, 2);
      l1 += __shfl_xor_sync(0xffffffffu, l1, 1); l1 += __shfl_xor_sync(0xffffffffu, l1, 2);
      const float i0 = 1.0f / l0, i1 = 1.0f / l1;
      uint32_t* op = reinterpret_cast<uint32_t*>(g_o + (size_t)row0 * DM + head * DH + (lane & 3) * 2);
#pragma unroll
      for (int g = 0; g < 4; g++) {
        op[g * 4] = pack_bf16(oacc[4 * g] * i0, oacc[4 * g + 1] * i0);
        op[8 * (DM / 2) + g * 4] = pack_bf16(oacc[4 * g + 2] * i1, oacc[4 * g + 3] * i1);
      }
    }
    if (t == 0) TL_END(1);
  }
}

typedef CUresult (*PFN_encodeTiled)(CUtensorMap*, CUtensorMapDataType, cuuint32_t, void*, const cuuint64_t*,
                                    const cuuint64_t*, const cuuint32_t*, const cuuint32_t*, CUtensorMapInterleave,
                                    CUtensorMapSwizzle, CUtensorMapL2promotion, CUtensorMapFloatOOBfill);

PFN_encodeTiled get_encode() {
  static PFN_encodeTiled fn = nullptr;
  if (!fn) {
    void* p = nullptr;
    cudaDriverEntryPointQueryResult st;
    cudaGetDriverEntryPoint("cuTensorMapEncodeTiled", &p, cudaEnableDefault, &st);
    fn = (PFN_encodeTiled)p;
  }
  return fn;
}

CUtensorMap tmap2d(const void* ptr, uint64_t rows, uint64_t cols, uint32_t bc, uint32_t br, CUtensorMapSwizzle sw) {
  CUtensorMap tm;
  cuuint64_t gd[2] = {cols, rows}; cuuint64_t gs[1] = {cols * 2}; cuuint32_t bx[2] = {bc, br}; cuuint32_t es[2] = {1, 1};
  get_encode()(&tm, CU_TENSOR_MAP_DATA_TYPE_BFLOAT16, 2, const_cast<void*>(ptr), gd, gs, bx, es,
               CU_TENSOR_MAP_INTERLEAVE_NONE, sw, CU_TENSOR_MAP_L2_PROMOTION_L2_128B, CU_TENSOR_MAP_FLOAT_OOB_FILL_NONE);
  return tm;
}
CUtensorMap tmapB(const void* ptr, uint64_t K, uint64_t N, uint32_t ch, uint32_t nchunks) {
  CUtensorMap tm;
  cuuint64_t gd[3] = {ch, K, N / ch}; cuuint64_t gs[2] = {N * 2, (cuuint64_t)ch * 2};
  cuuint32_t bx[3] = {ch, 64, nchunks}; cuuint32_t es[3] = {1, 1, 1};
  get_encode()(&tm, CU_TENSOR_MAP_DATA_TYPE_BFLOAT16, 3, const_cast<void*>(ptr), gd, gs, bx, es,
               CU_TENSOR_MAP_INTERLEAVE_NONE, ch == 64 ? CU_TENSOR_MAP_SWIZZLE_128B : CU_TENSOR_MAP_SWIZZLE_64B,
               CU_TENSOR_MAP_L2_PROMOTION_L2_128B, CU_TENSOR_MAP_FLOAT_OOB_FILL_NONE);
  return tm;
}

template <typename T> T* sym_addr(const T& sym) {
  void* p = nullptr;
  cudaGetSymbolAddress(&p, sym);
  return reinterpret_cast<T*>(p);
}

template <typename... KArgs, typename... Args>
void launch(void (*kern)(KArgs...), dim3 grid, int threads, size_t smem, bool pdl, int cluster_x, Args... args) {
  cudaFuncSetAttribute(kern, cudaFuncAttributeMaxDynamicSharedMemorySize, (int)smem);
  cudaLaunchConfig_t cfg = {};
  cfg.gridDim = grid; cfg.blockDim = dim3(threads, 1, 1); cfg.dynamicSmemBytes = smem; cfg.stream = cudaStreamPerThread;
  cudaLaunchAttribute at[2];
  int na = 0;
  if (pdl) { at[na].id = cudaLaunchAttributeProgrammaticStreamSerialization; at[na].val.programmaticStreamSerializationAllowed = 1; na++; }
  if (cluster_x > 1) {
    at[na].id = cudaLaunchAttributeClusterDimension;
    at[na].val.clusterDim.x = cluster_x; at[na].val.clusterDim.y = 1; at[na].val.clusterDim.z = 1; na++;
  }
  cfg.attrs = at; cfg.numAttrs = na;
  cudaLaunchKernelEx(&cfg, kern, KArgs(args)...);
}

#define USE_PDL 1

}

extern "C" void kernel_launch(void* const* d_in, const int* in_sizes, int n_in, void* d_out, int out_size) {
  (void)in_sizes; (void)n_in; (void)out_size;
  const bf16* x = (const bf16*)d_in[0];
  const bf16* wqkv = (const bf16*)d_in[1];
  const bf16* wo = (const bf16*)d_in[2];
  const bf16* w1 = (const bf16*)d_in[4];
  const bf16* b1 = (const bf16*)d_in[5];
  const bf16* w2 = (const bf16*)d_in[6];
  const bf16* b2 = (const bf16*)d_in[7];
  bf16* out = (bf16*)d_out;
  bf16* qkv = (bf16*)sym_addr(g_qkv);
  bf16* o = (bf16*)sym_addr(g_o);
  bf16* h = (bf16*)sym_addr(g_h);
  bf16* h1 = (bf16*)sym_addr(g_h1);
  const CUtensorMapSwizzle S128 = CU_TENSOR_MAP_SWIZZLE_128B, S64 = CU_TENSOR_MAP_SWIZZLE_64B;

  {
    CUtensorMap tA = tmap2d(x, SEQ, DM, 64, 256, S128), tB = tmapB(wqkv, DM, 3 * DM, 64, 3);
    CUtensorMap tC = tmap2d(qkv, SEQ, 3 * DM, 64, 128, S128);
    launch(gemm_kernel<EPI_QKV>, dim3(16, 8), 384, GLay<EPI_QKV>::TOTAL, false, 1, tA, tB, tC, tC, x, wqkv, (const bf16*)nullptr);
  }
  {
    CUtensorMap tKV = tmap2d(qkv, SEQ, 3 * DM, 32, 128, S64);
    launch(attn_kernel, dim3(128), 640, AT_SMEM, USE_PDL, 1, tKV, w1);
  }
  {
    CUtensorMap tA = tmap2d(o, SEQ, DM, 64, 128, S128), tB = tmapB(wo, DM, DM, 64, 2);
    CUtensorMap tR = tmap2d(x, SEQ, DM, 64, 64, S128), tC = tmap2d(h, SEQ, DM, 64, 64, S128);
    launch(gemm_kernel<EPI_OPROJ>, dim3(8, 16), 384, GLay<EPI_OPROJ>::TOTAL, USE_PDL, 2, tA, tB, tR, tC,
           (const bf16*)nullptr, (const bf16*)nullptr, (const bf16*)nullptr);
  }
  {
    CUtensorMap tA = tmap2d(h, SEQ, DM, 64, 128, S128), tB = tmapB(w1, DM, DFF, 32, 7);
    CUtensorMap tC = tmap2d(h1, SEQ, DFF, 32, 64, S64);
    launch(gemm_kernel<EPI_FFN1>, dim3(8, 16), 384, GLay<EPI_FFN1>::TOTAL, USE_PDL, 1, tA, tB, tC, tC,
           (const bf16*)nullptr, (const bf16*)nullptr, b1);
  }
  {
    CUtensorMap tA = tmap2d(h1, SEQ, DFF, 64, 128, S128), tB = tmapB(w2, DFF, DM, 64, 2);
    CUtensorMap tR = tmap2d(h, SEQ, DM, 64, 64, S128), tC = tmap2d(out, SEQ, DM, 64, 64, S128);
    launch(gemm_kernel<EPI_FFN2>, dim3(8, 16), 384, GLay<EPI_FFN2>::TOTAL, USE_PDL, 2, tA, tB, tR, tC,
           (const bf16*)nullptr, (const bf16*)nullptr, b2);
  }
}
```

```cpp
#include <cuda_runtime.h>
#include <cuda_bf16.h>
#include <cuda.h>
#include <stdint.h>

#define WAIT_TIMEOUT 0

namespace {

typedef __nv_bfloat16 bf16;

__device__ __forceinline__ uint32_t smem_u32(const void* p) {
  return (uint32_t)__cvta_generic_to_shared(p);
}
__device__ __forceinline__ void mbar_init(uint32_t bar, uint32_t count) {
  asm volatile("mbarrier.init.shared::cta.b64 [%0], %1;" ::"r"(bar), "r"(count) : "memory");
}
__device__ __forceinline__ void fence_mbar_init() {
  asm volatile("fence.mbarrier_init.release.cluster;" ::: "memory");
}
__device__ __forceinline__ void fence_proxy_async() {
  asm volatile("fence.proxy.async.shared::cta;" ::: "memory");
}
__device__ __forceinline__ void mbar_expect_tx(uint32_t bar, uint32_t bytes) {
  asm volatile("mbarrier.arrive.expect_tx.shared::cta.b64 _, [%0], %1;" ::"r"(bar), "r"(bytes) : "memory");
}
__device__ __forceinline__ void mbar_arrive(uint32_t bar) {
  asm volatile("mbarrier.arrive.shared::cta.b64 _, [%0];" ::"r"(bar) : "memory");
}
__device__ __forceinline__ uint32_t mbar_try_wait(uint32_t bar, uint32_t parity) {
  uint32_t ok;
  asm volatile(
      "{\n.reg .pred p;\n"
      "mbarrier.try_wait.parity.shared::cta.b64 p, [%1], %2;\n"
      "selp.u32 %0, 1, 0, p;\n}"
      : "=r"(ok) : "r"(bar), "r"(parity) : "memory");
  return ok;
}
__device__ __forceinline__ void mbar_wait(uint32_t bar, uint32_t parity) {
  while (!mbar_try_wait(bar, parity)) {}
}
__device__ __forceinline__ void named_bar_sync(int id, int nthreads) {
  asm volatile("bar.sync %0, %1;" ::"r"(id), "r"(nthreads) : "memory");
}
__device__ __forceinline__ void prefetch_tmap(const CUtensorMap* tm) {
  asm volatile("prefetch.tensormap [%0];" ::"l"(tm) : "memory");
}
__device__ __forceinline__ void tma_load_2d(uint32_t dst, const CUtensorMap* tm, int c0, int c1, uint32_t bar) {
  asm volatile(
      "cp.async.bulk.tensor.2d.shared::cluster.global.mbarrier::complete_tx::bytes [%0], [%1, {%3, %4}], [%2];"
      ::"r"(dst), "l"(tm), "r"(bar), "r"(c0), "r"(c1) : "memory");
}
__device__ __forceinline__ void tma_load_3d(uint32_t dst, const CUtensorMap* tm, int c0, int c1, int c2, uint32_t bar) {
  asm volatile(
      "cp.async.bulk.tensor.3d.shared::cluster.global.mbarrier::complete_tx::bytes [%0], [%1, {%3, %4, %5}], [%2];"
      ::"r"(dst), "l"(tm), "r"(bar), "r"(c0), "r"(c1), "r"(c2) : "memory");
}
__device__ __forceinline__ void tma_store_2d(const CUtensorMap* tm, uint32_t src, int c0, int c1) {
  asm volatile("cp.async.bulk.tensor.2d.global.shared::cta.bulk_group [%0, {%2, %3}], [%1];"
               ::"l"(tm), "r"(src), "r"(c0), "r"(c1) : "memory");
}
__device__ __forceinline__ void tma_store_commit() { asm volatile("cp.async.bulk.commit_group;" ::: "memory"); }
template <int N> __device__ __forceinline__ void tma_store_wait_read() {
  asm volatile("cp.async.bulk.wait_group.read %0;" ::"n"(N) : "memory");
}
__device__ __forceinline__ void wgmma_fence() { asm volatile("wgmma.fence.sync.aligned;" ::: "memory"); }
__device__ __forceinline__ void wgmma_commit() { asm volatile("wgmma.commit_group.sync.aligned;" ::: "memory"); }
template <int N> __device__ __forceinline__ void wgmma_wait() {
  asm volatile("wgmma.wait_group.sync.aligned %0;" ::"n"(N) : "memory");
}
template <int R> __device__ __forceinline__ void reg_alloc() {
  asm volatile("setmaxnreg.inc.sync.aligned.u32 %0;" ::"n"(R));
}
template <int R> __device__ __forceinline__ void reg_dealloc() {
  asm volatile("setmaxnreg.dec.sync.aligned.u32 %0;" ::"n"(R));
}
__device__ __forceinline__ void stmatrix_x4(uint32_t addr, uint32_t r0, uint32_t r1, uint32_t r2, uint32_t r3) {
  asm volatile("stmatrix.sync.aligned.m8n8.x4.shared.b16 [%0], {%1, %2, %3, %4};"
               ::"r"(addr), "r"(r0), "r"(r1), "r"(r2), "r"(r3) : "memory");
}
__device__ __forceinline__ void ldmatrix_x4(uint32_t addr, uint32_t& r0, uint32_t& r1, uint32_t& r2, uint32_t& r3) {
  asm volatile("ldmatrix.sync.aligned.m8n8.x4.shared.b16 {%0, %1, %2, %3}, [%4];"
               : "=r"(r0), "=r"(r1), "=r"(r2), "=r"(r3) : "r"(addr) : "memory");
}
__device__ __forceinline__ uint32_t pack_bf16(float lo, float hi) {
  uint32_t r;
  asm("cvt.rn.bf16x2.f32 %0, %1, %2;" : "=r"(r) : "f"(hi), "f"(lo));
  return r;
}
__device__ __forceinline__ float bf_lo(uint32_t p) { return __uint_as_float(p << 16); }
__device__ __forceinline__ float bf_hi(uint32_t p) { return __uint_as_float(p & 0xffff0000u); }
__device__ __forceinline__ float ex2_approx(float x) {
  float y;
  asm("ex2.approx.ftz.f32 %0, %1;" : "=f"(y) : "f"(x));
  return y;
}
__device__ __forceinline__ float tanh_approx(float x) {
  float y;
  asm("tanh.approx.f32 %0, %1;" : "=f"(y) : "f"(x));
  return y;
}
__device__ __forceinline__ void griddep_wait() { asm volatile("griddepcontrol.wait;" ::: "memory"); }
__device__ __forceinline__ void griddep_launch() { asm volatile("griddepcontrol.launch_dependents;" ::: "memory"); }
__device__ __forceinline__ unsigned ld_acquire(const unsigned* p) {
  unsigned v;
  asm volatile("ld.acquire.gpu.global.u32 %0, [%1];" : "=r"(v) : "l"(p) : "memory");
  return v;
}
__device__ __forceinline__ float warp_sum(float v) {
#pragma unroll
  for (int o = 16; o > 0; o >>= 1) v += __shfl_xor_sync(0xffffffffu, v, o);
  return v;
}
__device__ __forceinline__ uint64_t make_desc(uint32_t saddr, uint32_t lbo_bytes, uint32_t sbo_bytes, int swz  ) {
  uint64_t d = 0;
  d |= (uint64_t)((saddr & 0x3FFFF) >> 4);
  d |= (uint64_t)((lbo_bytes >> 4) & 0x3FFF) << 16;
  d |= (uint64_t)((sbo_bytes >> 4) & 0x3FFF) << 32;
  d |= (uint64_t)swz << 62;
  return d;
}

template <int TNSPB>
__device__ __forceinline__ void wgmma_ss_n128(float (&d)[64], uint64_t da, uint64_t db, int scale_d) {
  asm volatile("{\n.reg .pred p;\nsetp.ne.b32 p, %66, 0;\n"
    "wgmma.mma_async.sync.aligned.m64n128k16.f32.bf16.bf16 {%0, %1, %2, %3, %4, %5, %6, %7, %8, %9, %10, %11, %12, %13, %14, %15, %16, %17, %18, %19, %20, %21, %22, %23, %24, %25, %26, %27, %28, %29, %30, %31, %32, %33, %34, %35, %36, %37, %38, %39, %40, %41, %42, %43, %44, %45, %46, %47, %48, %49, %50, %51, %52, %53, %54, %55, %56, %57, %58, %59, %60, %61, %62, %63}, %64, %65, p, 1, 1, 0, %67;\n}"
    : "+f"(d[0]), "+f"(d[1]), "+f"(d[2]), "+f"(d[3]), "+f"(d[4]), "+f"(d[5]), "+f"(d[6]), "+f"(d[7]), "+f"(d[8]), "+f"(d[9]), "+f"(d[10]), "+f"(d[11]), "+f"(d[12]), "+f"(d[13]), "+f"(d[14]), "+f"(d[15]), "+f"(d[16]), "+f"(d[17]), "+f"(d[18]), "+f"(d[19]), "+f"(d[20]), "+f"(d[21]), "+f"(d[22]), "+f"(d[23]), "+f"(d[24]), "+f"(d[25]), "+f"(d[26]), "+f"(d[27]), "+f"(d[28]), "+f"(d[29]), "+f"(d[30]), "+f"(d[31]), "+f"(d[32]), "+f"(d[33]), "+f"(d[34]), "+f"(d[35]), "+f"(d[36]), "+f"(d[37]), "+f"(d[38]), "+f"(d[39]), "+f"(d[40]), "+f"(d[41]), "+f"(d[42]), "+f"(d[43]), "+f"(d[44]), "+f"(d[45]), "+f"(d[46]), "+f"(d[47]), "+f"(d[48]), "+f"(d[49]), "+f"(d[50]), "+f"(d[51]), "+f"(d[52]), "+f"(d[53]), "+f"(d[54]), "+f"(d[55]), "+f"(d[56]), "+f"(d[57]), "+f"(d[58]), "+f"(d[59]), "+f"(d[60]), "+f"(d[61]), "+f"(d[62]), "+f"(d[63])
    : "l"(da), "l"(db), "r"(scale_d), "n"(TNSPB));
}
template <int TNSPB>
__device__ __forceinline__ void wgmma_ss_n192(float (&d)[96], uint64_t da, uint64_t db, int scale_d) {
  asm volatile("{\n.reg .pred p;\nsetp.ne.b32 p, %98, 0;\n"
    "wgmma.mma_async.sync.aligned.m64n192k16.f32.bf16.bf16 {%0, %1, %2, %3, %4, %5, %6, %7, %8, %9, %10, %11, %12, %13, %14, %15, %16, %17, %18, %19, %20, %21, %22, %23, %24, %25, %26, %27, %28, %29, %30, %31, %32, %33, %34, %35, %36, %37, %38, %39, %40, %41, %42, %43, %44, %45, %46, %47, %48, %49, %50, %51, %52, %53, %54, %55, %56, %57, %58, %59, %60, %61, %62, %63, %64, %65, %66, %67, %68, %69, %70, %71, %72, %73, %74, %75, %76, %77, %78, %79, %80, %81, %82, %83, %84, %85, %86, %87, %88, %89, %90, %91, %92, %93, %94, %95}, %96, %97, p, 1, 1, 0, %99;\n}"
    : "+f"(d[0]), "+f"(d[1]), "+f"(d[2]), "+f"(d[3]), "+f"(d[4]), "+f"(d[5]), "+f"(d[6]), "+f"(d[7]), "+f"(d[8]), "+f"(d[9]), "+f"(d[10]), "+f"(d[11]), "+f"(d[12]), "+f"(d[13]), "+f"(d[14]), "+f"(d[15]), "+f"(d[16]), "+f"(d[17]), "+f"(d[18]), "+f"(d[19]), "+f"(d[20]), "+f"(d[21]), "+f"(d[22]), "+f"(d[23]), "+f"(d[24]), "+f"(d[25]), "+f"(d[26]), "+f"(d[27]), "+f"(d[28]), "+f"(d[29]), "+f"(d[30]), "+f"(d[31]), "+f"(d[32]), "+f"(d[33]), "+f"(d[34]), "+f"(d[35]), "+f"(d[36]), "+f"(d[37]), "+f"(d[38]), "+f"(d[39]), "+f"(d[40]), "+f"(d[41]), "+f"(d[42]), "+f"(d[43]), "+f"(d[44]), "+f"(d[45]), "+f"(d[46]), "+f"(d[47]), "+f"(d[48]), "+f"(d[49]), "+f"(d[50]), "+f"(d[51]), "+f"(d[52]), "+f"(d[53]), "+f"(d[54]), "+f"(d[55]), "+f"(d[56]), "+f"(d[57]), "+f"(d[58]), "+f"(d[59]), "+f"(d[60]), "+f"(d[61]), "+f"(d[62]), "+f"(d[63]), "+f"(d[64]), "+f"(d[65]), "+f"(d[66]), "+f"(d[67]), "+f"(d[68]), "+f"(d[69]), "+f"(d[70]), "+f"(d[71]), "+f"(d[72]), "+f"(d[73]), "+f"(d[74]), "+f"(d[75]), "+f"(d[76]), "+f"(d[77]), "+f"(d[78]), "+f"(d[79]), "+f"(d[80]), "+f"(d[81]), "+f"(d[82]), "+f"(d[83]), "+f"(d[84]), "+f"(d[85]), "+f"(d[86]), "+f"(d[87]), "+f"(d[88]), "+f"(d[89]), "+f"(d[90]), "+f"(d[91]), "+f"(d[92]), "+f"(d[93]), "+f"(d[94]), "+f"(d[95])
    : "l"(da), "l"(db), "r"(scale_d), "n"(TNSPB));
}
template <int TNSPB>
__device__ __forceinline__ void wgmma_ss_n224(float (&d)[112], uint64_t da, uint64_t db, int scale_d) {
  asm volatile("{\n.reg .pred p;\nsetp.ne.b32 p, %114, 0;\n"
    "wgmma.mma_async.sync.aligned.m64n224k16.f32.bf16.bf16 {%0, %1, %2, %3, %4, %5, %6, %7, %8, %9, %10, %11, %12, %13, %14, %15, %16, %17, %18, %19, %20, %21, %22, %23, %24, %25, %26, %27, %28, %29, %30, %31, %32, %33, %34, %35, %36, %37, %38, %39, %40, %41, %42, %43, %44, %45, %46, %47, %48, %49, %50, %51, %52, %53, %54, %55, %56, %57, %58, %59, %60, %61, %62, %63, %64, %65, %66, %67, %68, %69, %70, %71, %72, %73, %74, %75, %76, %77, %78, %79, %80, %81, %82, %83, %84, %85, %86, %87, %88, %89, %90, %91, %92, %93, %94, %95, %96, %97, %98, %99, %100, %101, %102, %103, %104, %105, %106, %107, %108, %109, %110, %111}, %112, %113, p, 1, 1, 0, %115;\n}"
    : "+f"(d[0]), "+f"(d[1]), "+f"(d[2]), "+f"(d[3]), "+f"(d[4]), "+f"(d[5]), "+f"(d[6]), "+f"(d[7]), "+f"(d[8]), "+f"(d[9]), "+f"(d[10]), "+f"(d[11]), "+f"(d[12]), "+f"(d[13]), "+f"(d[14]), "+f"(d[15]), "+f"(d[16]), "+f"(d[17]), "+f"(d[18]), "+f"(d[19]), "+f"(d[20]), "+f"(d[21]), "+f"(d[22]), "+f"(d[23]), "+f"(d[24]), "+f"(d[25]), "+f"(d[26]), "+f"(d[27]), "+f"(d[28]), "+f"(d[29]), "+f"(d[30]), "+f"(d[31]), "+f"(d[32]), "+f"(d[33]), "+f"(d[34]), "+f"(d[35]), "+f"(d[36]), "+f"(d[37]), "+f"(d[38]), "+f"(d[39]), "+f"(d[40]), "+f"(d[41]), "+f"(d[42]), "+f"(d[43]), "+f"(d[44]), "+f"(d[45]), "+f"(d[46]), "+f"(d[47]), "+f"(d[48]), "+f"(d[49]), "+f"(d[50]), "+f"(d[51]), "+f"(d[52]), "+f"(d[53]), "+f"(d[54]), "+f"(d[55]), "+f"(d[56]), "+f"(d[57]), "+f"(d[58]), "+f"(d[59]), "+f"(d[60]), "+f"(d[61]), "+f"(d[62]), "+f"(d[63]), "+f"(d[64]), "+f"(d[65]), "+f"(d[66]), "+f"(d[67]), "+f"(d[68]), "+f"(d[69]), "+f"(d[70]), "+f"(d[71]), "+f"(d[72]), "+f"(d[73]), "+f"(d[74]), "+f"(d[75]), "+f"(d[76]), "+f"(d[77]), "+f"(d[78]), "+f"(d[79]), "+f"(d[80]), "+f"(d[81]), "+f"(d[82]), "+f"(d[83]), "+f"(d[84]), "+f"(d[85]), "+f"(d[86]), "+f"(d[87]), "+f"(d[88]), "+f"(d[89]), "+f"(d[90]), "+f"(d[91]), "+f"(d[92]), "+f"(d[93]), "+f"(d[94]), "+f"(d[95]), "+f"(d[96]), "+f"(d[97]), "+f"(d[98]), "+f"(d[99]), "+f"(d[100]), "+f"(d[101]), "+f"(d[102]), "+f"(d[103]), "+f"(d[104]), "+f"(d[105]), "+f"(d[106]), "+f"(d[107]), "+f"(d[108]), "+f"(d[109]), "+f"(d[110]), "+f"(d[111])
    : "l"(da), "l"(db), "r"(scale_d), "n"(TNSPB));
}
template <int TNSPB>
__device__ __forceinline__ void wgmma_rs_n64(float (&d)[32], uint32_t a0, uint32_t a1, uint32_t a2, uint32_t a3, uint64_t db, int scale_d) {
  asm volatile("{\n.reg .pred p;\nsetp.ne.b32 p, %37, 0;\n"
    "wgmma.mma_async.sync.aligned.m64n64k16.f32.bf16.bf16 {%0, %1, %2, %3, %4, %5, %6, %7, %8, %9, %10, %11, %12, %13, %14, %15, %16, %17, %18, %19, %20, %21, %22, %23, %24, %25, %26, %27, %28, %29, %30, %31}, {%32, %33, %34, %35}, %36, p, 1, 1, %38;\n}"
    : "+f"(d[0]), "+f"(d[1]), "+f"(d[2]), "+f"(d[3]), "+f"(d[4]), "+f"(d[5]), "+f"(d[6]), "+f"(d[7]), "+f"(d[8]), "+f"(d[9]), "+f"(d[10]), "+f"(d[11]), "+f"(d[12]), "+f"(d[13]), "+f"(d[14]), "+f"(d[15]), "+f"(d[16]), "+f"(d[17]), "+f"(d[18]), "+f"(d[19]), "+f"(d[20]), "+f"(d[21]), "+f"(d[22]), "+f"(d[23]), "+f"(d[24]), "+f"(d[25]), "+f"(d[26]), "+f"(d[27]), "+f"(d[28]), "+f"(d[29]), "+f"(d[30]), "+f"(d[31])
    : "r"(a0), "r"(a1), "r"(a2), "r"(a3), "l"(db), "r"(scale_d), "n"(TNSPB));
}
template <int TNSPB>
__device__ __forceinline__ void wgmma_rs_n40(float (&d)[20], uint32_t a0, uint32_t a1, uint32_t a2, uint32_t a3, uint64_t db, int scale_d) {
  asm volatile("{\n.reg .pred p;\nsetp.ne.b32 p, %25, 0;\n"
    "wgmma.mma_async.sync.aligned.m64n40k16.f32.bf16.bf16 {%0, %1, %2, %3, %4, %5, %6, %7, %8, %9, %10, %11, %12, %13, %14, %15, %16, %17, %18, %19}, {%20, %21, %22, %23}, %24, p, 1, 1, %26;\n}"
    : "+f"(d[0]), "+f"(d[1]), "+f"(d[2]), "+f"(d[3]), "+f"(d[4]), "+f"(d[5]), "+f"(d[6]), "+f"(d[7]), "+f"(d[8]), "+f"(d[9]), "+f"(d[10]), "+f"(d[11]), "+f"(d[12]), "+f"(d[13]), "+f"(d[14]), "+f"(d[15]), "+f"(d[16]), "+f"(d[17]), "+f"(d[18]), "+f"(d[19])
    : "r"(a0), "r"(a1), "r"(a2), "r"(a3), "l"(db), "r"(scale_d), "n"(TNSPB));
}
template <int N, int TNSPB> __device__ __forceinline__ void wgmma_ss(float (&d)[N/2], uint64_t da, uint64_t db, int scale_d) {
  if constexpr (N == 128) wgmma_ss_n128<TNSPB>(d, da, db, scale_d);
  if constexpr (N == 192) wgmma_ss_n192<TNSPB>(d, da, db, scale_d);
  if constexpr (N == 224) wgmma_ss_n224<TNSPB>(d, da, db, scale_d);
}
template <int N, int TNSPB> __device__ __forceinline__ void wgmma_rs(float (&d)[N/2], uint32_t a0, uint32_t a1, uint32_t a2, uint32_t a3, uint64_t db, int scale_d) {
  if constexpr (N == 64) wgmma_rs_n64<TNSPB>(d, a0, a1, a2, a3, db, scale_d);
  if constexpr (N == 40) wgmma_rs_n40<TNSPB>(d, a0, a1, a2, a3, db, scale_d);
}

constexpr int SEQ = 2048, DM = 1024, NH = 32, DH = 32, DFF = 3584;

__device__ __align__(1024) bf16 g_qkv[SEQ * 3 * DM];
__device__ __align__(1024) bf16 g_o[SEQ * DM];
__device__ __align__(1024) bf16 g_h[SEQ * DM];
__device__ __align__(1024) bf16 g_h1[SEQ * DFF];
__device__ float2 g_ln1[SEQ];
__device__ float g_cs1[24 * 3 * DM];
__device__ float g_cs2[DFF];
__device__ float2 g_ln2[SEQ * 8];
__device__ unsigned g_cnt[32];

#define TL_START(k) do {} while (0)
#define TL_END(k) do {} while (0)

enum { EPI_QKV = 0, EPI_OPROJ = 1, EPI_FFN1 = 2, EPI_FFN2 = 3 };
template <int EPI> struct GCfg;
template <> struct GCfg<EPI_QKV>   { static constexpr int BM = 256, BN = 192, ST = 4, CH = 64, NT = 1, KB = 16, RBUF = 0; };
template <> struct GCfg<EPI_OPROJ> { static constexpr int BM = 128, BN = 128, ST = 5, CH = 64, NT = 1, KB = 16, RBUF = 1; };
template <> struct GCfg<EPI_FFN1>  { static constexpr int BM = 128, BN = 224, ST = 4, CH = 32, NT = 2, KB = 16, RBUF = 0; };
template <> struct GCfg<EPI_FFN2>  { static constexpr int BM = 128, BN = 128, ST = 5, CH = 64, NT = 1, KB = 56, RBUF = 1; };

template <int EPI> struct GLay {
  using C = GCfg<EPI>;
  static constexpr uint32_t A_BYTES = C::BM * 128, B_BYTES = C::BN * 128, STAGE = A_BYTES + B_BYTES;
  static constexpr uint32_t R_OFF = C::ST * STAGE;
  static constexpr uint32_t R_BYTES = C::RBUF ? C::BM * C::BN * 2 : 0;
  static constexpr uint32_t BAR_OFF = R_OFF + R_BYTES;
  static constexpr uint32_t AUX_OFF = BAR_OFF + 128;
  static_assert(8 * (2 * C::ST + 2) <= 128, "barrier area");
  static constexpr uint32_t AUX_BYTES = (EPI == EPI_QKV) ? 192 * 4 : (EPI == EPI_FFN1) ? (128 * 8 + 448 * 8) : 0;
  static constexpr uint32_t TOTAL = AUX_OFF + AUX_BYTES + 1024;
};

__device__ __forceinline__ void qkv_aux(const bf16* __restrict__ x, const bf16* __restrict__ w, float* colp_s,
                                        uint32_t epi_bar) {
  const int at = threadIdx.x - 32, aw = at >> 5, lane = at & 31;
  const int mb = blockIdx.y, nb = blockIdx.x, n0 = nb * 192;
  for (int i = aw; i < 16; i += 3) {
    const int row = mb * 256 + nb * 16 + i;
    const uint4* p = reinterpret_cast<const uint4*>(x + (size_t)row * DM) + lane;
    uint4 v[4];
#pragma unroll
    for (int q = 0; q < 4; q++) v[q] = __ldg(p + q * 32);
    float s = 0.f;
#pragma unroll
    for (int q = 0; q < 4; q++)
      s += (bf_lo(v[q].x) + bf_hi(v[q].x)) + (bf_lo(v[q].y) + bf_hi(v[q].y)) + (bf_lo(v[q].z) + bf_hi(v[q].z)) +
           (bf_lo(v[q].w) + bf_hi(v[q].w));
    const float mean = warp_sum(s) * (1.0f / DM);
    float ss = 0.f;
#pragma unroll
    for (int q = 0; q < 4; q++) {
      const uint32_t u[4] = {v[q].x, v[q].y, v[q].z, v[q].w};
#pragma unroll
      for (int e = 0; e < 4; e++) {
        const float a = bf_lo(u[e]) - mean, b = bf_hi(u[e]) - mean;
        ss = fmaf(a, a, ss); ss = fmaf(b, b, ss);
      }
    }
    const float var = warp_sum(ss) * (1.0f / DM);
    const float rstd = 1.0f / sqrtf(var + 1e-5f);
    if (lane == 0) g_ln1[row] = make_float2(rstd, -mean * rstd);
  }
  {
    float c[6] = {0.f, 0.f, 0.f, 0.f, 0.f, 0.f};
    const uint32_t* wp = reinterpret_cast<const uint32_t*>(w + (size_t)(mb * 128) * (3 * DM) + n0) + lane;
#pragma unroll 4
    for (int kk = aw; kk < 128; kk += 3) {
      const uint32_t* r = wp + (size_t)kk * (3 * DM / 2);
      const uint32_t a0 = __ldg(r), a1 = __ldg(r + 32), a2 = __ldg(r + 64);
      c[0] += bf_lo(a0); c[1] += bf_hi(a0); c[2] += bf_lo(a1); c[3] += bf_hi(a1); c[4] += bf_lo(a2); c[5] += bf_hi(a2);
    }
    float2* dst = reinterpret_cast<float2*>(g_cs1 + (size_t)(mb * 3 + aw) * (3 * DM) + n0) + lane;
    dst[0] = make_float2(c[0], c[1]); dst[32] = make_float2(c[2], c[3]); dst[64] = make_float2(c[4], c[5]);
  }
  __threadfence();
  __syncwarp();
  if (lane == 0) { atomicAdd(&g_cnt[mb], 1u); atomicAdd(&g_cnt[8 + nb], 1u); }
  if (lane == 0) {
    int n = 0;
    while (ld_acquire(&g_cnt[mb]) < 48u || ld_acquire(&g_cnt[8 + nb]) < 24u) {
      __nanosleep(64);
    }
    (void)n;
  }
  __syncwarp();
  {
    float2 acc = make_float2(0.f, 0.f);
    const float2* src = reinterpret_cast<const float2*>(g_cs1 + n0) + at;
#pragma unroll 8
    for (int p = 0; p < 24; p++) {
      const float2 v = __ldcg(src + (size_t)p * (3 * DM / 2));
      acc.x += v.x; acc.y += v.y;
    }
    reinterpret_cast<float2*>(colp_s)[at] = acc;
  }
  mbar_arrive(epi_bar);
}

__device__ __forceinline__ void ffn1_aux(const bf16* __restrict__ b1, float2* rowp_s, float2* colp_s, int m0, int n0,
                                         uint32_t epi_bar) {
  const int at = threadIdx.x - 32;
  griddep_wait();
  for (int r = at; r < 128; r += 96) {
    const float4* p = reinterpret_cast<const float4*>(g_ln2 + (size_t)(m0 + r) * 8);
    float4 v[4];
#pragma unroll
    for (int q = 0; q < 4; q++) v[q] = __ldcg(p + q);
    float mean = 0.f, m2 = 0.f;
#pragma unroll
    for (int q = 0; q < 4; q++) { mean += v[q].x + v[q].z; m2 += v[q].y + v[q].w; }
    mean *= 0.125f;
#pragma unroll
    for (int q = 0; q < 4; q++) {
      const float a = v[q].x - mean, b = v[q].z - mean;
      m2 = fmaf(128.f * a, a, m2); m2 = fmaf(128.f * b, b, m2);
    }
    const float rstd = 1.0f / sqrtf(m2 * (1.0f / DM) + 1e-5f);
    rowp_s[r] = make_float2(rstd, -mean * rstd);
  }
  for (int c = at; c < 448; c += 96) colp_s[c] = make_float2(__ldcg(&g_cs2[n0 + c]), __bfloat162float(b1[n0 + c]));
  mbar_arrive(epi_bar);
}

__device__ __forceinline__ float gelu_tanh(float t) {
  const float u = t * fmaf(t * t, 0.7978845608028654f * 0.044715f, 0.7978845608028654f);
  const float h = 0.5f * t;
  return fmaf(h, tanh_approx(u), h);
}

template <int EPI>
__global__ void __launch_bounds__(384, 1)
gemm_kernel(const __grid_constant__ CUtensorMap tmA, const __grid_constant__ CUtensorMap tmB,
            const __grid_constant__ CUtensorMap tmR, const __grid_constant__ CUtensorMap tmC,
            const bf16* __restrict__ px, const bf16* __restrict__ pw, const bf16* __restrict__ pbias) {
  using C = GCfg<EPI>;
  using L = GLay<EPI>;
  constexpr int BM = C::BM, BN = C::BN, ST = C::ST, CH = C::CH, NT = C::NT, KB = C::KB;
  constexpr int MI = BM / 128;
  constexpr int SWZ = (CH == 64) ? 1 : 2;
  constexpr int CB = CH * 2;
  constexpr int CPC = CH / 8;
  static_assert(C::RBUF || (KB % ST == 0 && 2 * L::STAGE >= BM * BN * 2), "borrowed staging");
  extern __shared__ uint8_t smem_raw[];
  const uint32_t sbase = (smem_u32(smem_raw) + 1023u) & ~1023u;
  const uint32_t bar_base = sbase + L::BAR_OFF;
  auto full_bar = [&](int s) { return bar_base + 8u * s; };
  auto empty_bar = [&](int s) { return bar_base + 8u * (ST + s); };
  const uint32_t epi_bar = bar_base + 8u * (2 * ST), res_bar = epi_bar + 8u;
  uint8_t* aux_s = smem_raw + (sbase - smem_u32(smem_raw)) + L::AUX_OFF;

  const int warp = threadIdx.x >> 5, lane = threadIdx.x & 31;
  const int m0 = blockIdx.y * BM, n0 = blockIdx.x * (BN * NT);
  TL_START(EPI == EPI_QKV ? 0 : EPI + 1);

  if (threadIdx.x == 0) {
    for (int s = 0; s < ST; s++) { mbar_init(full_bar(s), 1); mbar_init(empty_bar(s), 2); }
    mbar_init(epi_bar, 96);
    mbar_init(res_bar, 1);
    fence_mbar_init();
    prefetch_tmap(&tmA); prefetch_tmap(&tmB); prefetch_tmap(&tmC);
    if (C::RBUF) prefetch_tmap(&tmR);
  }
  __syncthreads();
  griddep_launch();

  if (warp < 4) {
    reg_dealloc<40>();
    if (warp == 0) {
      if (lane == 0) {
        for (int s = 0; s < ST; s++) {
          mbar_expect_tx(full_bar(s), L::STAGE);
          tma_load_3d(sbase + s * L::STAGE + L::A_BYTES, &tmB, 0, s * 64, n0 / CH, full_bar(s));
        }
        griddep_wait();
        for (int s = 0; s < ST; s++) tma_load_2d(sbase + s * L::STAGE, &tmA, s * 64, m0, full_bar(s));
        if (C::RBUF) {
          mbar_expect_tx(res_bar, L::R_BYTES);
#pragma unroll
          for (int c = 0; c < BN / 64; c++)
#pragma unroll
            for (int w = 0; w < BM / 64; w++)
              tma_load_2d(sbase + L::R_OFF + c * (BM * 128) + w * (64 * 128), &tmR, n0 + c * 64, m0 + w * 64, res_bar);
        }
        int s = 0; uint32_t ph = 1;
        for (int it = ST; it < NT * KB; it++) {
          const int tile = it / KB, kb = it % KB;
          mbar_wait(empty_bar(s), ph ^ 1);
          mbar_expect_tx(full_bar(s), L::STAGE);
          tma_load_2d(sbase + s * L::STAGE, &tmA, kb * 64, m0, full_bar(s));
          tma_load_3d(sbase + s * L::STAGE + L::A_BYTES, &tmB, 0, kb * 64, (n0 + tile * BN) / CH, full_bar(s));
          if (++s == ST) { s = 0; ph ^= 1; }
        }
      }
    } else {
      if constexpr (EPI == EPI_QKV) qkv_aux(px, pw, reinterpret_cast<float*>(aux_s), epi_bar);
      if constexpr (EPI == EPI_FFN1)
        ffn1_aux(pbias, reinterpret_cast<float2*>(aux_s), reinterpret_cast<float2*>(aux_s + 128 * 8), m0, n0, epi_bar);
    }
  } else {
    reg_alloc<232>();
    const int wgc = (warp >> 2) - 1, w4 = warp & 3;
    const int t = threadIdx.x & 127;
    const int q2 = (lane & 3) * 2;
    uint32_t bias2[(EPI == EPI_FFN2) ? BN / 8 : 1];
    if constexpr (EPI == EPI_FFN2) {
#pragma unroll
      for (int g = 0; g < BN / 8; g++) bias2[g] = __ldg(reinterpret_cast<const uint32_t*>(pbias + n0 + g * 8 + q2));
    }
    int s = 0; uint32_t ph = 0;
    for (int tile = 0; tile < NT; tile++) {
      float acc[MI][BN / 2];
      int prev_s = 0;
      for (int kb = 0; kb < KB; kb++) {
        mbar_wait(full_bar(s), ph);
        const uint32_t sa = sbase + s * L::STAGE, sb = sa + L::A_BYTES;
        wgmma_fence();
#pragma unroll
        for (int k16 = 0; k16 < 4; k16++) {
          const uint64_t db = make_desc(sb + k16 * (16 * CB), 64 * CB, 8 * CB, SWZ);
#pragma unroll
          for (int mi = 0; mi < MI; mi++) {
            const uint64_t da = make_desc(sa + (wgc * (BM / 2) + mi * 64) * 128 + k16 * 32, 16, 1024, 1);
            wgmma_ss<BN, 1>(acc[mi], da, db, (kb | k16) != 0);
          }
        }
        wgmma_commit();
        wgmma_wait<1>();
        if (kb > 0 && (C::RBUF || kb < KB - 1) && t == 0) mbar_arrive(empty_bar(prev_s));
        prev_s = s;
        if (++s == ST) { s = 0; ph ^= 1; }
      }
      wgmma_wait<0>();
      uint32_t stg;
      if constexpr (C::RBUF) {
        stg = sbase + L::R_OFF;
        mbar_wait(res_bar, 0);
      } else {
        stg = sbase + (ST - 2) * L::STAGE;
        named_bar_sync(1, 256);
        if (tile == 0) mbar_wait(epi_bar, 0);
      }
      const int nt0 = n0 + tile * BN;
#pragma unroll
      for (int mi = 0; mi < MI; mi++) {
        const int rl0 = wgc * (BM / 2) + mi * 64 + w4 * 16 + (lane >> 2);
        const int rs = wgc * (BM / 2) + mi * 64 + w4 * 16 + (lane & 7) + ((lane >> 3) & 1) * 8;
        const int rsw = (CH == 64) ? (rs & 7) : ((rs >> 1) & 3);
        float2 rp0, rp1;
        if constexpr (EPI == EPI_QKV) { rp0 = __ldcg(&g_ln1[m0 + rl0]); rp1 = __ldcg(&g_ln1[m0 + rl0 + 8]); }
        if constexpr (EPI == EPI_FFN1) {
          rp0 = reinterpret_cast<const float2*>(aux_s)[rl0]; rp1 = reinterpret_cast<const float2*>(aux_s)[rl0 + 8];
        }
#pragma unroll
        for (int jj = 0; jj < BN / 16; jj++) {
          float* d = &acc[mi][jj * 8];
          const int cg = 2 * jj + (lane >> 4);
          const uint32_t addr = stg + (cg / CPC) * (BM * CB) + rs * CB + (((cg % CPC) ^ rsw) << 4);
          uint32_t p0, p1, p2, p3;
          if constexpr (EPI == EPI_QKV) {
            const float* colp = reinterpret_cast<const float*>(aux_s);
            const float2 ca = *reinterpret_cast<const float2*>(colp + jj * 16 + q2);
            const float2 cb = *reinterpret_cast<const float2*>(colp + jj * 16 + 8 + q2);
            p0 = pack_bf16(fmaf(d[0], rp0.x, rp0.y * ca.x), fmaf(d[1], rp0.x, rp0.y * ca.y));
            p1 = pack_bf16(fmaf(d[2], rp1.x, rp1.y * ca.x), fmaf(d[3], rp1.x, rp1.y * ca.y));
            p2 = pack_bf16(fmaf(d[4], rp0.x, rp0.y * cb.x), fmaf(d[5], rp0.x, rp0.y * cb.y));
            p3 = pack_bf16(fmaf(d[6], rp1.x, rp1.y * cb.x), fmaf(d[7], rp1.x, rp1.y * cb.y));
          } else if constexpr (EPI == EPI_FFN1) {
            const float2* colp = reinterpret_cast<const float2*>(aux_s + 128 * 8) + tile * BN;
            const float4 ca = *reinterpret_cast<const float4*>(colp + jj * 16 + q2);
            const float4 cb = *reinterpret_cast<const float4*>(colp + jj * 16 + 8 + q2);
            p0 = pack_bf16(gelu_tanh(fmaf(d[0], rp0.x, fmaf(rp0.y, ca.x, ca.y))), gelu_tanh(fmaf(d[1], rp0.x, fmaf(rp0.y, ca.z, ca.w))));
            p1 = pack_bf16(gelu_tanh(fmaf(d[2], rp1.x, fmaf(rp1.y, ca.x, ca.y))), gelu_tanh(fmaf(d[3], rp1.x, fmaf(rp1.y, ca.z, ca.w))));
            p2 = pack_bf16(gelu_tanh(fmaf(d[4], rp0.x, fmaf(rp0.y, cb.x, cb.y))), gelu_tanh(fmaf(d[5], rp0.x, fmaf(rp0.y, cb.z, cb.w))));
            p3 = pack_bf16(gelu_tanh(fmaf(d[6], rp1.x, fmaf(rp1.y, cb.x, cb.y))), gelu_tanh(fmaf(d[7], rp1.x, fmaf(rp1.y, cb.z, cb.w))));
          } else {
            uint32_t r0, r1, r2, r3;
            ldmatrix_x4(addr, r0, r1, r2, r3);
            float b0 = 0.f, b1 = 0.f, b2 = 0.f, b3 = 0.f;
            if constexpr (EPI == EPI_FFN2) {
              b0 = bf_lo(bias2[2 * jj]); b1 = bf_hi(bias2[2 * jj]); b2 = bf_lo(bias2[2 * jj + 1]); b3 = bf_hi(bias2[2 * jj + 1]);
            }
            p0 = pack_bf16(d[0] + b0 + bf_lo(r0), d[1] + b1 + bf_hi(r0));
            p1 = pack_bf16(d[2] + b0 + bf_lo(r1), d[3] + b1 + bf_hi(r1));
            p2 = pack_bf16(d[4] + b2 + bf_lo(r2), d[5] + b3 + bf_hi(r2));
            p3 = pack_bf16(d[6] + b2 + bf_lo(r3), d[7] + b3 + bf_hi(r3));
            if constexpr (EPI == EPI_OPROJ) {
              d[0] = bf_lo(p0); d[1] = bf_hi(p0); d[2] = bf_lo(p1); d[3] = bf_hi(p1);
              d[4] = bf_lo(p2); d[5] = bf_hi(p2); d[6] = bf_lo(p3); d[7] = bf_hi(p3);
            }
          }
          stmatrix_x4(addr, p0, p1, p2, p3);
        }
        if constexpr (EPI == EPI_OPROJ) {
          float s0 = 0.f, s1 = 0.f;
#pragma unroll
          for (int jj = 0; jj < BN / 16; jj++) {
            const float* d = &acc[mi][jj * 8];
            s0 += (d[0] + d[1]) + (d[4] + d[5]); s1 += (d[2] + d[3]) + (d[6] + d[7]);
          }
          s0 += __shfl_xor_sync(0xffffffffu, s0, 1); s0 += __shfl_xor_sync(0xffffffffu, s0, 2);
          s1 += __shfl_xor_sync(0xffffffffu, s1, 1); s1 += __shfl_xor_sync(0xffffffffu, s1, 2);
          const float mu0 = s0 * (1.0f / BN), mu1 = s1 * (1.0f / BN);
          float v0 = 0.f, v1 = 0.f;
#pragma unroll
          for (int jj = 0; jj < BN / 16; jj++) {
            const float* d = &acc[mi][jj * 8];
            float a;
            a = d[0] - mu0; v0 = fmaf(a, a, v0); a = d[1] - mu0; v0 = fmaf(a, a, v0);
            a = d[4] - mu0; v0 = fmaf(a, a, v0); a = d[5] - mu0; v0 = fmaf(a, a, v0);
            a = d[2] - mu1; v1 = fmaf(a, a, v1); a = d[3] - mu1; v1 = fmaf(a, a, v1);
            a = d[6] - mu1; v1 = fmaf(a, a, v1); a = d[7] - mu1; v1 = fmaf(a, a, v1);
          }
          v0 += __shfl_xor_sync(0xffffffffu, v0, 1); v0 += __shfl_xor_sync(0xffffffffu, v0, 2);
          v1 += __shfl_xor_sync(0xffffffffu, v1, 1); v1 += __shfl_xor_sync(0xffffffffu, v1, 2);
          if ((lane & 3) == 0) {
            g_ln2[(size_t)(m0 + rl0) * 8 + blockIdx.x] = make_float2(mu0, v0);
            g_ln2[(size_t)(m0 + rl0 + 8) * 8 + blockIdx.x] = make_float2(mu1, v1);
          }
        }
      }
      fence_proxy_async();
      named_bar_sync(2 + wgc, 128);
      if (t == 0) {
#pragma unroll
        for (int c = 0; c < BN / CH; c++)
          tma_store_2d(&tmC, stg + c * (BM * CB) + wgc * (BM / 2) * CB, nt0 + c * CH, m0 + wgc * (BM / 2));
        tma_store_commit();
        tma_store_wait_read<0>();
        if constexpr (!C::RBUF) { mbar_arrive(empty_bar(ST - 2)); mbar_arrive(empty_bar(ST - 1)); }
      }
    }
    if (t == 0) TL_END(EPI == EPI_QKV ? 0 : EPI + 1);
  }
}

constexpr int AT_ST = 4;
constexpr uint32_t AT_ONES = AT_ST * 16384;
constexpr uint32_t AT_BAR = AT_ONES + 4096;
constexpr uint32_t AT_SMEM = AT_BAR + 8 * 2 * AT_ST + 1024;
constexpr uint64_t AT_DESC_HI = ((uint64_t)2 << 62) | ((uint64_t)(512 >> 4) << 32);

struct AttnBlk {
  float sc[32];
  float oa[20];
  uint32_t q[8];
  float m0, m1;
};

__device__ __forceinline__ void attn_qk(AttnBlk& b, uint32_t klo) {
  wgmma_rs<64, 0>(b.sc, b.q[0], b.q[1], b.q[2], b.q[3], AT_DESC_HI | (uint64_t)(klo | (1u << 16)), 0);
  wgmma_rs<64, 0>(b.sc, b.q[4], b.q[5], b.q[6], b.q[7], AT_DESC_HI | (uint64_t)((klo + 2) | (1u << 16)), 1);
}

__device__ __forceinline__ void attn_max(AttnBlk& b, float& mc0, float& mc1, float& a0, float& a1, bool& moved) {
  const float SC = 0.17677669529663687f * 1.4426950408889634f;
  float mx0 = fmaxf(b.sc[0], b.sc[1]), mx1 = fmaxf(b.sc[2], b.sc[3]);
#pragma unroll
  for (int g = 1; g < 8; g++) {
    mx0 = fmaxf(mx0, fmaxf(b.sc[4 * g], b.sc[4 * g + 1]));
    mx1 = fmaxf(mx1, fmaxf(b.sc[4 * g + 2], b.sc[4 * g + 3]));
  }
  mx0 = fmaxf(mx0, __shfl_xor_sync(0xffffffffu, mx0, 1)); mx0 = fmaxf(mx0, __shfl_xor_sync(0xffffffffu, mx0, 2));
  mx1 = fmaxf(mx1, __shfl_xor_sync(0xffffffffu, mx1, 1)); mx1 = fmaxf(mx1, __shfl_xor_sync(0xffffffffu, mx1, 2));
  const float mn0 = fmaxf(b.m0, mx0), mn1 = fmaxf(b.m1, mx1);
  moved = __any_sync(0xffffffffu, (mn0 != b.m0) || (mn1 != b.m1));
  a0 = ex2_approx((b.m0 - mn0) * SC); a1 = ex2_approx((b.m1 - mn1) * SC);
  b.m0 = mn0; b.m1 = mn1;
  mc0 = mn0 * SC; mc1 = mn1 * SC;
}
__device__ __forceinline__ float ex2_approx_v(float x) {
  float y;
  asm("ex2.approx.ftz.f32 %0, %1;" : "=f"(y) : "f"(x));
  return y;
}
__device__ __forceinline__ void attn_exp(AttnBlk& b, uint32_t (&p)[16], float mc0, float mc1) {
  const float SC = 0.17677669529663687f * 1.4426950408889634f;
#pragma unroll
  for (int g = 0; g < 8; g++) {
    const float e0 = ex2_approx_v(fmaf(b.sc[4 * g], SC, -mc0)), e1 = ex2_approx_v(fmaf(b.sc[4 * g + 1], SC, -mc0));
    const float e2 = ex2_approx_v(fmaf(b.sc[4 * g + 2], SC, -mc1)), e3 = ex2_approx_v(fmaf(b.sc[4 * g + 3], SC, -mc1));
    p[2 * g] = pack_bf16(e0, e1);
    p[2 * g + 1] = pack_bf16(e2, e3);
  }
}
__device__ __forceinline__ void named_bar_arrive(int id, int nthreads) {
  asm volatile("bar.arrive %0, %1;" ::"r"(id), "r"(nthreads) : "memory");
}
__device__ __forceinline__ void attn_wait1(uint32_t (&p)[16]) {
  asm volatile("wgmma.wait_group.sync.aligned 1;"
               : "+r"(p[0]), "+r"(p[1]), "+r"(p[2]), "+r"(p[3]), "+r"(p[4]), "+r"(p[5]), "+r"(p[6]), "+r"(p[7]),
                 "+r"(p[8]), "+r"(p[9]), "+r"(p[10]), "+r"(p[11]), "+r"(p[12]), "+r"(p[13]), "+r"(p[14]), "+r"(p[15])
               :: "memory");
}
__device__ __forceinline__ void attn_pv(AttnBlk& b, const uint32_t (&p)[16], float a0, float a1, bool moved, uint32_t vlo, int acc) {
  if (moved && acc) {
#pragma unroll
    for (int g = 0; g < 5; g++) {
      b.oa[4 * g] *= a0; b.oa[4 * g + 1] *= a0; b.oa[4 * g + 2] *= a1; b.oa[4 * g + 3] *= a1;
    }
  }
  wgmma_fence();
#pragma unroll
  for (int k = 0; k < 4; k++)
    wgmma_rs<40, 1>(b.oa, p[4 * k], p[4 * k + 1], p[4 * k + 2], p[4 * k + 3], AT_DESC_HI | (uint64_t)(vlo + k * 64), k > 0 ? 1 : acc);
}

__global__ void __launch_bounds__(640, 1)
attn_kernel(const __grid_constant__ CUtensorMap tmKV, const bf16* __restrict__ w1) {
  extern __shared__ uint8_t smem_raw[];
  const uint32_t sbase = (smem_u32(smem_raw) + 1023u) & ~1023u;
  const uint32_t bar_base = sbase + AT_BAR;
  auto full_bar = [&](int s) { return bar_base + 8u * s; };
  auto empty_bar = [&](int s) { return bar_base + 8u * (AT_ST + s); };
  const int warp = threadIdx.x >> 5, lane = threadIdx.x & 31;
  const int head = blockIdx.x >> 2, qb = blockIdx.x & 3;
  TL_START(1);

  if (threadIdx.x == 0) {
    for (int s = 0; s < AT_ST; s++) { mbar_init(full_bar(s), 1); mbar_init(empty_bar(s), 4); }
    fence_mbar_init();
    prefetch_tmap(&tmKV);
  }
  for (int i = threadIdx.x; i < 256; i += 640) {
    const int r = i >> 2, c = i & 3;
    const uint32_t v0 = (c == ((r >> 1) & 3)) ? 0x3F80u : 0u;
    asm volatile("st.shared.v4.u32 [%0], {%1, %2, %2, %2};" ::"r"(sbase + AT_ONES + i * 16), "r"(v0), "r"(0u) : "memory");
  }
  fence_proxy_async();
  __syncthreads();
  griddep_launch();

  if (warp < 4) {
    reg_dealloc<24>();
    if (warp == 0) {
      if (lane == 0) {
        griddep_wait();
        int s = 0; uint32_t ph = 0;
        for (int it = 0; it < 32; it++) {
          mbar_wait(empty_bar(s), ph ^ 1);
          mbar_expect_tx(full_bar(s), 16384);
          tma_load_2d(sbase + s * 16384, &tmKV, DM + head * DH, (it & 15) * 128, full_bar(s));
          tma_load_2d(sbase + s * 16384 + 8192, &tmKV, 2 * DM + head * DH, (it & 15) * 128, full_bar(s));
          if (++s == AT_ST) { s = 0; ph ^= 1; }
        }
      }
    } else if (warp == 1) {
      if (blockIdx.x < DFF / 32) {
        float cs[8];
#pragma unroll
        for (int i = 0; i < 8; i++) cs[i] = 0.f;
        const uint4* wp = reinterpret_cast<const uint4*>(w1 + (size_t)(lane >> 2) * DFF + blockIdx.x * 32 + (lane & 3) * 8);
#pragma unroll 4
        for (int i = 0; i < DM / 8; i++) {
          const uint4 v = __ldg(wp + (size_t)i * (8 * DFF / 8));
          cs[0] += bf_lo(v.x); cs[1] += bf_hi(v.x); cs[2] += bf_lo(v.y); cs[3] += bf_hi(v.y);
          cs[4] += bf_lo(v.z); cs[5] += bf_hi(v.z); cs[6] += bf_lo(v.w); cs[7] += bf_hi(v.w);
        }
#pragma unroll
        for (int i = 0; i < 8; i++) {
          cs[i] += __shfl_xor_sync(0xffffffffu, cs[i], 4);
          cs[i] += __shfl_xor_sync(0xffffffffu, cs[i], 8);
          cs[i] += __shfl_xor_sync(0xffffffffu, cs[i], 16);
        }
        if (lane < 4) {
          float4* dst = reinterpret_cast<float4*>(&g_cs2[blockIdx.x * 32 + lane * 8]);
          dst[0] = make_float4(cs[0], cs[1], cs[2], cs[3]);
          dst[1] = make_float4(cs[4], cs[5], cs[6], cs[7]);
        }
      }
    } else if (warp == 2) {
      griddep_wait();
      if (blockIdx.x == 0) g_cnt[lane] = 0u;
    }
  } else {
    reg_alloc<112>();
    const int wg = (warp >> 2) - 1, w4 = warp & 3;
    const int t = threadIdx.x & 127;
    griddep_wait();
    AttnBlk A;
#pragma unroll
    for (int i = 0; i < 20; i++) A.oa[i] = 0.f;
    int s = 0; uint32_t ph = 0;
    for (int pass = 0; pass < 2; pass++) {
      const int rowA = qb * 512 + pass * 256 + wg * 64 + w4 * 16 + (lane >> 2);
      {
        const uint32_t* qp = reinterpret_cast<const uint32_t*>(g_qkv + (size_t)rowA * (3 * DM) + head * DH + (lane & 3) * 2);
        constexpr int R8 = 8 * (3 * DM / 2);
#pragma unroll
        for (int k = 0; k < 2; k++) {
          A.q[4 * k] = __ldcg(qp + 8 * k); A.q[4 * k + 1] = __ldcg(qp + R8 + 8 * k);
          A.q[4 * k + 2] = __ldcg(qp + 8 * k + 4); A.q[4 * k + 3] = __ldcg(qp + R8 + 8 * k + 4);
        }
      }
      A.m0 = A.m1 = -INFINITY;
      mbar_wait(full_bar(s), ph);
      uint32_t klo = (sbase + s * 16384) >> 4;
      wgmma_fence();
      attn_qk(A, klo); wgmma_commit();
      wgmma_wait<0>();
      for (int j = 0; j < 32; j++) {
        const int half = j & 1;
        const uint32_t vlo = (klo + 512) | (((sbase + AT_ONES) >> 4) - (klo + 512)) << 16;
        uint32_t nklo = klo + 256;
        int ns = s; uint32_t nph = ph;
        if (half == 1) {
          if (++ns == AT_ST) { ns = 0; nph ^= 1; }
          nklo = (sbase + ns * 16384) >> 4;
        }
        uint32_t p[16]; float a0, a1, mc0, mc1; bool moved;
        attn_max(A, mc0, mc1, a0, a1, moved);
        attn_exp(A, p, mc0, mc1);
        if (j == 31) nklo = klo;
        else if (half == 1) mbar_wait(full_bar(ns), nph);
        attn_pv(A, p, a0, a1, moved, vlo, j > 0);
        attn_qk(A, nklo); wgmma_commit();
        wgmma_wait<0>();
        if (half == 1 && t == 0) mbar_arrive(empty_bar(s));
        klo = nklo; s = ns; ph = nph;
      }
      {
        const AttnBlk& b = A;
        const float l0 = __shfl_sync(0xffffffffu, b.oa[16], lane & ~3), l1 = __shfl_sync(0xffffffffu, b.oa[18], lane & ~3);
        const float i0 = 1.0f / l0, i1 = 1.0f / l1;
        uint32_t* op = reinterpret_cast<uint32_t*>(g_o + (size_t)rowA * DM + head * DH + (lane & 3) * 2);
#pragma unroll
        for (int g = 0; g < 4; g++) {
          op[g * 4] = pack_bf16(b.oa[4 * g] * i0, b.oa[4 * g + 1] * i0);
          op[8 * (DM / 2) + g * 4] = pack_bf16(b.oa[4 * g + 2] * i1, b.oa[4 * g + 3] * i1);
        }
      }
    }
    if (t == 0) TL_END(1);
  }
}

typedef CUresult (*PFN_encodeTiled)(CUtensorMap*, CUtensorMapDataType, cuuint32_t, void*, const cuuint64_t*,
                                    const cuuint64_t*, const cuuint32_t*, const cuuint32_t*, CUtensorMapInterleave,
                                    CUtensorMapSwizzle, CUtensorMapL2promotion, CUtensorMapFloatOOBfill);

PFN_encodeTiled get_encode() {
  static PFN_encodeTiled fn = nullptr;
  if (!fn) {
    void* p = nullptr;
    cudaDriverEntryPointQueryResult st;
    cudaGetDriverEntryPoint("cuTensorMapEncodeTiled", &p, cudaEnableDefault, &st);
    fn = (PFN_encodeTiled)p;
  }
  return fn;
}

CUtensorMap tmap2d(const void* ptr, uint64_t rows, uint64_t cols, uint32_t bc, uint32_t br, CUtensorMapSwizzle sw) {
  CUtensorMap tm;
  cuuint64_t gd[2] = {cols, rows}; cuuint64_t gs[1] = {cols * 2}; cuuint32_t bx[2] = {bc, br}; cuuint32_t es[2] = {1, 1};
  get_encode()(&tm, CU_TENSOR_MAP_DATA_TYPE_BFLOAT16, 2, const_cast<void*>(ptr), gd, gs, bx, es,
               CU_TENSOR_MAP_INTERLEAVE_NONE, sw, CU_TENSOR_MAP_L2_PROMOTION_L2_128B, CU_TENSOR_MAP_FLOAT_OOB_FILL_NONE);
  return tm;
}
CUtensorMap tmapB(const void* ptr, uint64_t K, uint64_t N, uint32_t ch, uint32_t nchunks) {
  CUtensorMap tm;
  cuuint64_t gd[3] = {ch, K, N / ch}; cuuint64_t gs[2] = {N * 2, (cuuint64_t)ch * 2};
  cuuint32_t bx[3] = {ch, 64, nchunks}; cuuint32_t es[3] = {1, 1, 1};
  get_encode()(&tm, CU_TENSOR_MAP_DATA_TYPE_BFLOAT16, 3, const_cast<void*>(ptr), gd, gs, bx, es,
               CU_TENSOR_MAP_INTERLEAVE_NONE, ch == 64 ? CU_TENSOR_MAP_SWIZZLE_128B : CU_TENSOR_MAP_SWIZZLE_64B,
               CU_TENSOR_MAP_L2_PROMOTION_L2_128B, CU_TENSOR_MAP_FLOAT_OOB_FILL_NONE);
  return tm;
}

template <typename T> T* sym_addr(const T& sym) {
  void* p = nullptr;
  cudaGetSymbolAddress(&p, sym);
  return reinterpret_cast<T*>(p);
}

template <typename... KArgs, typename... Args>
void launch(void (*kern)(KArgs...), dim3 grid, int threads, size_t smem, bool pdl, int cluster_x, Args... args) {
  cudaFuncSetAttribute(kern, cudaFuncAttributeMaxDynamicSharedMemorySize, (int)smem);
  cudaLaunchConfig_t cfg = {};
  cfg.gridDim = grid; cfg.blockDim = dim3(threads, 1, 1); cfg.dynamicSmemBytes = smem; cfg.stream = cudaStreamPerThread;
  cudaLaunchAttribute at[2];
  int na = 0;
  if (pdl) { at[na].id = cudaLaunchAttributeProgrammaticStreamSerialization; at[na].val.programmaticStreamSerializationAllowed = 1; na++; }
  if (cluster_x > 1) {
    at[na].id = cudaLaunchAttributeClusterDimension;
    at[na].val.clusterDim.x = cluster_x; at[na].val.clusterDim.y = 1; at[na].val.clusterDim.z = 1; na++;
  }
  cfg.attrs = at; cfg.numAttrs = na;
  cudaLaunchKernelEx(&cfg, kern, KArgs(args)...);
}

#define USE_PDL 1

}

extern "C" void kernel_launch(void* const* d_in, const int* in_sizes, int n_in, void* d_out, int out_size) {
  (void)in_sizes; (void)n_in; (void)out_size;
  const bf16* x = (const bf16*)d_in[0];
  const bf16* wqkv = (const bf16*)d_in[1];
  const bf16* wo = (const bf16*)d_in[2];
  const bf16* w1 = (const bf16*)d_in[4];
  const bf16* b1 = (const bf16*)d_in[5];
  const bf16* w2 = (const bf16*)d_in[6];
  const bf16* b2 = (const bf16*)d_in[7];
  bf16* out = (bf16*)d_out;
  bf16* qkv = (bf16*)sym_addr(g_qkv);
  bf16* o = (bf16*)sym_addr(g_o);
  bf16* h = (bf16*)sym_addr(g_h);
  bf16* h1 = (bf16*)sym_addr(g_h1);
  const CUtensorMapSwizzle S128 = CU_TENSOR_MAP_SWIZZLE_128B, S64 = CU_TENSOR_MAP_SWIZZLE_64B;

  {
    CUtensorMap tA = tmap2d(x, SEQ, DM, 64, 256, S128), tB = tmapB(wqkv, DM, 3 * DM, 64, 3);
    CUtensorMap tC = tmap2d(qkv, SEQ, 3 * DM, 64, 128, S128);
    launch(gemm_kernel<EPI_QKV>, dim3(16, 8), 384, GLay<EPI_QKV>::TOTAL, false, 1, tA, tB, tC, tC, x, wqkv, (const bf16*)nullptr);
  }
  {
    CUtensorMap tKV = tmap2d(qkv, SEQ, 3 * DM, 32, 128, S64);
    launch(attn_kernel, dim3(128), 640, AT_SMEM, USE_PDL, 1, tKV, w1);
  }
  {
    CUtensorMap tA = tmap2d(o, SEQ, DM, 64, 128, S128), tB = tmapB(wo, DM, DM, 64, 2);
    CUtensorMap tR = tmap2d(x, SEQ, DM, 64, 64, S128), tC = tmap2d(h, SEQ, DM, 64, 64, S128);
    launch(gemm_kernel<EPI_OPROJ>, dim3(8, 16), 384, GLay<EPI_OPROJ>::TOTAL, USE_PDL, 2, tA, tB, tR, tC,
           (const bf16*)nullptr, (const bf16*)nullptr, (const bf16*)nullptr);
  }
  {
    CUtensorMap tA = tmap2d(h, SEQ, DM, 64, 128, S128), tB = tmapB(w1, DM, DFF, 32, 7);
    CUtensorMap tC = tmap2d(h1, SEQ, DFF, 32, 64, S64);
    launch(gemm_kernel<EPI_FFN1>, dim3(8, 16), 384, GLay<EPI_FFN1>::TOTAL, USE_PDL, 1, tA, tB, tC, tC,
           (const bf16*)nullptr, (const bf16*)nullptr, b1);
  }
  {
    CUtensorMap tA = tmap2d(h1, SEQ, DFF, 64, 128, S128), tB = tmapB(w2, DFF, DM, 64, 2);
    CUtensorMap tR = tmap2d(h, SEQ, DM, 64, 64, S128), tC = tmap2d(out, SEQ, DM, 64, 64, S128);
    launch(gemm_kernel<EPI_FFN2>, dim3(8, 16), 384, GLay<EPI_FFN2>::TOTAL, USE_PDL, 2, tA, tB, tR, tC,
           (const bf16*)nullptr, (const bf16*)nullptr, b2);
  }
}
```
